```python
import torch

def _softmax(x, axis=-1):
    return torch.softmax(x, dim=axis)

def _gelu(x):
    return torch.nn.functional.gelu(x, approximate='tanh')

def _silu(x):
    return torch.nn.functional.silu(x)

def _sigmoid(x):
    return torch.sigmoid(x)

def _layernorm(x, axis=-1, eps=1e-05):
    m = x.mean(dim=axis, keepdim=True)
    v = x.var(dim=axis, keepdim=True, unbiased=False)
    return (x - m) / torch.sqrt(v + eps)

def _scatter_add(tgt, idx, src, axis=0):
    return tgt.clone().index_add_(axis, idx, src)

def _segment_sum(src, seg, n):
    out = torch.zeros((n,) + src.shape[1:], dtype=src.dtype)
    return out.index_add_(0, seg, src)

def _pad(x, pw):
    flat = tuple((v for pair in reversed(pw) for v in pair))
    return torch.nn.functional.pad(x, flat)
kernel_name = 'gated_mix__memory_aug_recurrent_mem_tr__dense_activation_squared_relu__prompt'

def setup_inputs():

    _w = lambda a: (lambda t: t.to(torch.bfloat16) if t.is_floating_point() else t)(torch.as_tensor(a))

    def _A_setup():
        B, S, Dm = (1, 2048, 1024)
        H, Dh = (32, 128)
        M, seg = (8, 32)
        seg = min(seg, S)
        S = S // seg * seg
        return {'x': _w((lambda *s: torch.randn(*s, dtype=torch.bfloat16) * 0.05)(B, S, Dm)), 'mem0': _w((lambda *s: torch.randn(*s, dtype=torch.bfloat16) * 0.8)(B, M, Dm)), 'Wq': _w((lambda *s: torch.randn(*s, dtype=torch.bfloat16) * 3.2)(Dm, H, Dh) * Dm ** (-0.5)), 'Wk': _w((lambda *s: torch.randn(*s, dtype=torch.bfloat16) * 3.2)(Dm, H, Dh) * Dm ** (-0.5)), 'Wv': _w((lambda *s: torch.randn(*s, dtype=torch.bfloat16) * 0.8)(Dm, H, Dh) * Dm ** (-0.5)), 'Wo': _w((lambda *s: torch.randn(*s, dtype=torch.bfloat16) * 0.8)(H, Dh, Dm) * (H * Dh) ** (-0.5)), 'seg_len': seg}
    _A_in = _A_setup()

    def _B_setup():
        B, S, D, F = (1, 2048, 1024, 3584)
        return {'x': _w((lambda *s: torch.randn(*s, dtype=torch.bfloat16) * 0.05)(B, S, D)), 'w1': _w((lambda *s: torch.randn(*s, dtype=torch.bfloat16) * 0.05)(D, F)), 'b1': _w((lambda *s: torch.randn(*s, dtype=torch.bfloat16) * 0.05)(F)), 'w2': _w((lambda *s: torch.randn(*s, dtype=torch.bfloat16) * 0.05)(F, D)), 'b2': _w((lambda *s: torch.randn(*s, dtype=torch.bfloat16) * 0.05)(D))}
    _B_in = _B_setup()
    return {'A_x': _A_in['x'], 'A_mem0': _A_in['mem0'], 'A_Wq': _A_in['Wq'], 'A_Wk': _A_in['Wk'], 'A_Wv': _A_in['Wv'], 'A_Wo': _A_in['Wo'], 'A_seg_len': _A_in['seg_len'], 'B_x': _B_in['x'], 'B_w1': _B_in['w1'], 'B_b1': _B_in['b1'], 'B_w2': _B_in['w2'], 'B_b2': _B_in['b2'], 'gate_w': _w((lambda *s: torch.randn(*s, dtype=torch.bfloat16) * 0.05)(1024) * 16.0)}

def reference(A_x, A_mem0, A_Wq, A_Wk, A_Wv, A_Wo, A_seg_len, B_x, B_w1, B_b1, B_w2, B_b2, gate_w):

    def _A_ref(x, mem0, Wq, Wk, Wv, Wo, seg_len):
        B, S, Dm = x.shape
        H, Dh = (Wq.shape[1], Wq.shape[2])
        M = mem0.shape[1]
        scale = Dh ** (-0.5)
        n_seg = S // seg_len
        L = M + seg_len
        idx = torch.arange(L)
        mask = (idx[:, None] < M) | (idx[:, None] >= idx[None, :])
        mem = mem0
        outs = []
        for s in range(n_seg):
            xs = x[:, s * seg_len:(s + 1) * seg_len, :].clone()
            h = torch.concatenate([mem, xs], axis=1)
            q = torch.einsum('btd,dhe->bhte', h, Wq)
            k = torch.einsum('btd,dhe->bhte', h, Wk)
            v = torch.einsum('btd,dhe->bhte', h, Wv)
            scores = torch.einsum('bhqe,bhke->bhqk', q, k) * scale
            scores = torch.where(mask[None, None], scores, -1000000000.0)
            p = _softmax(scores, axis=-1)
            o = torch.einsum('bhqk,bhke->bhqe', p, v)
            o = torch.einsum('bhte,hed->btd', o, Wo)
            mem = o[:, :M, :].clone()
            outs.append(o[:, M:, :])
        return torch.concatenate(outs, axis=1)

    def _B_ref(x, w1, b1, w2, b2):
        h = torch.einsum('bsd,df->bsf', x, w1) + b1
        zero = torch.zeros_like(h)
        r = torch.where(h > zero, h, zero)
        h = r * r
        out = torch.einsum('bsf,fd->bsd', h, w2) + b2
        return out
    x = A_x
    g = _sigmoid((x * gate_w).sum(-1, keepdims=True))
    a = _A_ref(x, A_mem0, A_Wq, A_Wk, A_Wv, A_Wo, A_seg_len)
    b = _B_ref(x, B_w1, B_b1, B_w2, B_b2)
    return g * a + (1 - g) * b
```

```cpp
#include <cuda_runtime.h>
#include <cuda_bf16.h>
#include <cuda.h>
#include <stdint.h>

#define PROF 0
#define EXP_W 1
#define EXP_T 1
#define EXP_S 1
#define EXP_K 1
#define STPOS 0
#define XTMA 0
#define D_EX 250
#define D_P1 550
#define D_MEM 320
#define PROFM 0xffff
#define PROFA 0xfff

namespace {

constexpr int S_ = 2048, D_ = 1024, H_ = 32, DH_ = 128, HD_ = 4096, F_ = 3584, NSEG = 64;

constexpr uint32_t OFF_P1 = 32u * 65536u;
constexpr uint32_t OFF_XP = OFF_P1 + 128u * 16384u;
constexpr uint32_t OFF_MEM = OFF_XP + 32u * 262144u;
constexpr uint32_t OFF_SELT = OFF_MEM + 65536u;
constexpr uint32_t OFF_MEM0 = OFF_SELT + 1024u;
constexpr uint32_t COMM_BYTES = OFF_MEM0 + 16384u;

__device__ __align__(1024) unsigned char g_comm_raw[COMM_BYTES + 131072];
__device__ __align__(1024) __nv_bfloat16 g_h[(size_t)S_ * F_];
__device__ __align__(1024) __nv_bfloat16 g_ox[(size_t)S_ * HD_];
__device__ float g_gate[S_];
__device__ int g_err;

__device__ __forceinline__ uint32_t smem_u32(const void* p) { return (uint32_t)__cvta_generic_to_shared(p); }
__device__ __forceinline__ void mbar_init(uint32_t bar, uint32_t cnt) { asm volatile("mbarrier.init.shared::cta.b64 [%0], %1;" :: "r"(bar), "r"(cnt) : "memory"); }
__device__ __forceinline__ void mbar_expect_tx(uint32_t bar, uint32_t bytes) { asm volatile("mbarrier.arrive.expect_tx.shared::cta.b64 _, [%0], %1;" :: "r"(bar), "r"(bytes) : "memory"); }
__device__ __forceinline__ void mbar_arrive(uint32_t bar) { asm volatile("mbarrier.arrive.shared::cta.b64 _, [%0];" :: "r"(bar) : "memory"); }
__device__ __forceinline__ bool mbar_try(uint32_t bar, uint32_t parity) {
    uint32_t ok;
    asm volatile("{ .reg .pred p; mbarrier.try_wait.parity.shared::cta.b64 p, [%1], %2; selp.u32 %0, 1, 0, p; }" : "=r"(ok) : "r"(bar), "r"(parity) : "memory");
    return ok != 0;
}
__device__ __forceinline__ void mbar_wait(uint32_t bar, uint32_t parity) {
    int guard = 0;
    while (!mbar_try(bar, parity)) { if (++guard > (1 << 20)) { g_err = 1; break; } }
}
__device__ __forceinline__ void tma_2d(uint32_t dst, const CUtensorMap* map, int c0, int c1, uint32_t bar) {
    asm volatile("cp.async.bulk.tensor.2d.shared::cluster.global.mbarrier::complete_tx::bytes [%0], [%1, {%3, %4}], [%2];"
                 :: "r"(dst), "l"(map), "r"(bar), "r"(c0), "r"(c1) : "memory");
}
__device__ __forceinline__ void tma_3d(uint32_t dst, const CUtensorMap* map, int c0, int c1, int c2, uint32_t bar) {
    asm volatile("cp.async.bulk.tensor.3d.shared::cluster.global.mbarrier::complete_tx::bytes [%0], [%1, {%3, %4, %5}], [%2];"
                 :: "r"(dst), "l"(map), "r"(bar), "r"(c0), "r"(c1), "r"(c2) : "memory");
}
__device__ __forceinline__ void bulk_g2s(uint32_t dst, const void* src, uint32_t bytes, uint32_t bar) {
    asm volatile("cp.async.bulk.shared::cluster.global.mbarrier::complete_tx::bytes [%0], [%1], %2, [%3];"
                 :: "r"(dst), "l"(src), "r"(bytes), "r"(bar) : "memory");
}
__device__ __forceinline__ uint64_t mkdesc(uint32_t addr, uint32_t lbo, uint32_t sbo, uint32_t swz) {
    return (uint64_t)((addr & 0x3FFFF) >> 4) | ((uint64_t)(lbo >> 4) << 16) | ((uint64_t)(sbo >> 4) << 32) | ((uint64_t)swz << 62);
}
#define WG_FENCE()   asm volatile("wgmma.fence.sync.aligned;" ::: "memory")
#define WG_COMMIT()  asm volatile("wgmma.commit_group.sync.aligned;" ::: "memory")
#define WG_WAIT(n)   asm volatile("wgmma.wait_group.sync.aligned %0;" :: "n"(n) : "memory")
__device__ __forceinline__ void bar_sync(int id, int n) { asm volatile("bar.sync %0, %1;" :: "r"(id), "r"(n) : "memory"); }
__device__ __forceinline__ void bar_arrive(int id, int n) { asm volatile("bar.arrive %0, %1;" :: "r"(id), "r"(n) : "memory"); }
__device__ __forceinline__ void fence_async_smem() { asm volatile("fence.proxy.async.shared::cta;" ::: "memory"); }
__device__ __forceinline__ uint32_t pack_bf16(float lo, float hi) {
    uint32_t r; asm("cvt.rn.bf16x2.f32 %0, %1, %2;" : "=r"(r) : "f"(hi), "f"(lo)); return r;
}
__device__ __forceinline__ uint32_t hadd2_bf16(uint32_t a, uint32_t b) {
    uint32_t r; asm("add.rn.bf16x2 %0, %1, %2;" : "=r"(r) : "r"(a), "r"(b)); return r;
}
__device__ __forceinline__ float bf_lo(uint32_t w) { return __uint_as_float(w << 16); }
__device__ __forceinline__ float bf_hi(uint32_t w) { return __uint_as_float(w & 0xffff0000u); }
__device__ __forceinline__ uint32_t movm(uint32_t a) {
    uint32_t d; asm volatile("movmatrix.sync.aligned.m8n8.trans.b16 %0, %1;" : "=r"(d) : "r"(a)); return d;
}
__device__ __forceinline__ void ldsm4(uint32_t (&r)[4], uint32_t addr) {
    asm volatile("ldmatrix.sync.aligned.m8n8.x4.shared.b16 {%0,%1,%2,%3}, [%4];" : "=r"(r[0]), "=r"(r[1]), "=r"(r[2]), "=r"(r[3]) : "r"(addr) : "memory");
}
__device__ __forceinline__ void ldsm4t(uint32_t (&r)[4], uint32_t addr) {
    asm volatile("ldmatrix.sync.aligned.m8n8.x4.trans.shared.b16 {%0,%1,%2,%3}, [%4];" : "=r"(r[0]), "=r"(r[1]), "=r"(r[2]), "=r"(r[3]) : "r"(addr) : "memory");
}
__device__ __forceinline__ void ldsm2(uint32_t (&r)[2], uint32_t addr) {
    asm volatile("ldmatrix.sync.aligned.m8n8.x2.shared.b16 {%0,%1}, [%2];" : "=r"(r[0]), "=r"(r[1]) : "r"(addr) : "memory");
}
__device__ __forceinline__ void stsm4(uint32_t addr, uint32_t a, uint32_t b, uint32_t c, uint32_t d) {
    asm volatile("stmatrix.sync.aligned.m8n8.x4.shared.b16 [%0], {%1,%2,%3,%4};" :: "r"(addr), "r"(a), "r"(b), "r"(c), "r"(d) : "memory");
}
__device__ __forceinline__ void mma16816(float (&d)[4], uint32_t a0, uint32_t a1, uint32_t a2, uint32_t a3, uint32_t b0, uint32_t b1) {
    asm volatile("mma.sync.aligned.m16n8k16.row.col.f32.bf16.bf16.f32 {%0,%1,%2,%3}, {%4,%5,%6,%7}, {%8,%9}, {%0,%1,%2,%3};"
                 : "+f"(d[0]), "+f"(d[1]), "+f"(d[2]), "+f"(d[3]) : "r"(a0), "r"(a1), "r"(a2), "r"(a3), "r"(b0), "r"(b1));
}
__device__ __forceinline__ void mma1688(float (&d)[4], uint32_t a0, uint32_t a1, uint32_t b0) {
    asm volatile("mma.sync.aligned.m16n8k8.row.col.f32.bf16.bf16.f32 {%0,%1,%2,%3}, {%4,%5}, {%6}, {%0,%1,%2,%3};"
                 : "+f"(d[0]), "+f"(d[1]), "+f"(d[2]), "+f"(d[3]) : "r"(a0), "r"(a1), "r"(b0));
}
__device__ __forceinline__ uint4 ldg_rlx4(const void* p) {
    uint4 v; asm volatile("ld.relaxed.gpu.global.v4.u32 {%0,%1,%2,%3}, [%4];" : "=r"(v.x), "=r"(v.y), "=r"(v.z), "=r"(v.w) : "l"(p) : "memory"); return v;
}
__device__ __forceinline__ uint2 ldg_rlx2(const void* p) {
    uint2 v; asm volatile("ld.relaxed.gpu.global.v2.u32 {%0,%1}, [%2];" : "=r"(v.x), "=r"(v.y) : "l"(p) : "memory"); return v;
}
__device__ __forceinline__ void stg_rlx4(void* p, uint32_t a, uint32_t b, uint32_t c, uint32_t d) {
    asm volatile("st.relaxed.gpu.global.v4.u32 [%0], {%1,%2,%3,%4};" :: "l"(p), "r"(a), "r"(b), "r"(c), "r"(d) : "memory");
}
__device__ __forceinline__ void stg_rlx2(void* p, uint32_t a, uint32_t b) {
    asm volatile("st.relaxed.gpu.global.v2.u32 [%0], {%1,%2};" :: "l"(p), "r"(a), "r"(b) : "memory");
}
__device__ __forceinline__ void stg_rlx1(void* p, uint32_t a) {
    asm volatile("st.relaxed.gpu.global.u32 [%0], %1;" :: "l"(p), "r"(a) : "memory");
}
__device__ __forceinline__ uint32_t ldg_acq1(const void* p) {
    uint32_t v; asm volatile("ld.acquire.gpu.global.u32 %0, [%1];" : "=r"(v) : "l"(p) : "memory"); return v;
}
__device__ __forceinline__ void red_rel_add(void* p, uint32_t v) {
    asm volatile("red.release.gpu.global.add.u32 [%0], %1;" :: "l"(p), "r"(v) : "memory");
}
__device__ __forceinline__ uint32_t clk32() { uint32_t c; asm volatile("mov.u32 %0, %%clock;" : "=r"(c) :: "memory"); return c; }
__device__ __forceinline__ unsigned char* comm_base() {
    return (unsigned char*)(((uintptr_t)g_comm_raw + 65535) & ~(uintptr_t)65535);
}

__device__ __forceinline__ void wgmma_n224_kn(float (&d)[112], uint64_t da, uint64_t db, int sd) {
    asm volatile("{ .reg .pred p; setp.ne.b32 p, %114, 0;\n"
        "wgmma.mma_async.sync.aligned.m64n224k16.f32.bf16.bf16 {%0,%1,%2,%3,%4,%5,%6,%7,%8,%9,%10,%11,%12,%13,%14,%15,%16,%17,%18,%19,%20,%21,%22,%23,%24,%25,%26,%27,%28,%29,%30,%31,%32,%33,%34,%35,%36,%37,%38,%39,%40,%41,%42,%43,%44,%45,%46,%47,%48,%49,%50,%51,%52,%53,%54,%55,%56,%57,%58,%59,%60,%61,%62,%63,%64,%65,%66,%67,%68,%69,%70,%71,%72,%73,%74,%75,%76,%77,%78,%79,%80,%81,%82,%83,%84,%85,%86,%87,%88,%89,%90,%91,%92,%93,%94,%95,%96,%97,%98,%99,%100,%101,%102,%103,%104,%105,%106,%107,%108,%109,%110,%111}, %112, %113, p, 1, 1, 0, 1; }"
        : "+f"(d[0]),"+f"(d[1]),"+f"(d[2]),"+f"(d[3]),"+f"(d[4]),"+f"(d[5]),"+f"(d[6]),"+f"(d[7]),"+f"(d[8]),"+f"(d[9]),"+f"(d[10]),"+f"(d[11]),"+f"(d[12]),"+f"(d[13]),"+f"(d[14]),"+f"(d[15]),"+f"(d[16]),"+f"(d[17]),"+f"(d[18]),"+f"(d[19]),"+f"(d[20]),"+f"(d[21]),"+f"(d[22]),"+f"(d[23]),"+f"(d[24]),"+f"(d[25]),"+f"(d[26]),"+f"(d[27]),"+f"(d[28]),"+f"(d[29]),"+f"(d[30]),"+f"(d[31]),"+f"(d[32]),"+f"(d[33]),"+f"(d[34]),"+f"(d[35]),"+f"(d[36]),"+f"(d[37]),"+f"(d[38]),"+f"(d[39]),"+f"(d[40]),"+f"(d[41]),"+f"(d[42]),"+f"(d[43]),"+f"(d[44]),"+f"(d[45]),"+f"(d[46]),"+f"(d[47]),"+f"(d[48]),"+f"(d[49]),"+f"(d[50]),"+f"(d[51]),"+f"(d[52]),"+f"(d[53]),"+f"(d[54]),"+f"(d[55]),"+f"(d[56]),"+f"(d[57]),"+f"(d[58]),"+f"(d[59]),"+f"(d[60]),"+f"(d[61]),"+f"(d[62]),"+f"(d[63]),"+f"(d[64]),"+f"(d[65]),"+f"(d[66]),"+f"(d[67]),"+f"(d[68]),"+f"(d[69]),"+f"(d[70]),"+f"(d[71]),"+f"(d[72]),"+f"(d[73]),"+f"(d[74]),"+f"(d[75]),"+f"(d[76]),"+f"(d[77]),"+f"(d[78]),"+f"(d[79]),"+f"(d[80]),"+f"(d[81]),"+f"(d[82]),"+f"(d[83]),"+f"(d[84]),"+f"(d[85]),"+f"(d[86]),"+f"(d[87]),"+f"(d[88]),"+f"(d[89]),"+f"(d[90]),"+f"(d[91]),"+f"(d[92]),"+f"(d[93]),"+f"(d[94]),"+f"(d[95]),"+f"(d[96]),"+f"(d[97]),"+f"(d[98]),"+f"(d[99]),"+f"(d[100]),"+f"(d[101]),"+f"(d[102]),"+f"(d[103]),"+f"(d[104]),"+f"(d[105]),"+f"(d[106]),"+f"(d[107]),"+f"(d[108]),"+f"(d[109]),"+f"(d[110]),"+f"(d[111])
        : "l"(da), "l"(db), "r"(sd));
}
__device__ __forceinline__ void wgmma_n128_kn(float (&d)[64], uint64_t da, uint64_t db, int sd) {
    asm volatile("{ .reg .pred p; setp.ne.b32 p, %66, 0;\n"
        "wgmma.mma_async.sync.aligned.m64n128k16.f32.bf16.bf16 {%0,%1,%2,%3,%4,%5,%6,%7,%8,%9,%10,%11,%12,%13,%14,%15,%16,%17,%18,%19,%20,%21,%22,%23,%24,%25,%26,%27,%28,%29,%30,%31,%32,%33,%34,%35,%36,%37,%38,%39,%40,%41,%42,%43,%44,%45,%46,%47,%48,%49,%50,%51,%52,%53,%54,%55,%56,%57,%58,%59,%60,%61,%62,%63}, %64, %65, p, 1, 1, 0, 1; }"
        : "+f"(d[0]),"+f"(d[1]),"+f"(d[2]),"+f"(d[3]),"+f"(d[4]),"+f"(d[5]),"+f"(d[6]),"+f"(d[7]),"+f"(d[8]),"+f"(d[9]),"+f"(d[10]),"+f"(d[11]),"+f"(d[12]),"+f"(d[13]),"+f"(d[14]),"+f"(d[15]),"+f"(d[16]),"+f"(d[17]),"+f"(d[18]),"+f"(d[19]),"+f"(d[20]),"+f"(d[21]),"+f"(d[22]),"+f"(d[23]),"+f"(d[24]),"+f"(d[25]),"+f"(d[26]),"+f"(d[27]),"+f"(d[28]),"+f"(d[29]),"+f"(d[30]),"+f"(d[31]),"+f"(d[32]),"+f"(d[33]),"+f"(d[34]),"+f"(d[35]),"+f"(d[36]),"+f"(d[37]),"+f"(d[38]),"+f"(d[39]),"+f"(d[40]),"+f"(d[41]),"+f"(d[42]),"+f"(d[43]),"+f"(d[44]),"+f"(d[45]),"+f"(d[46]),"+f"(d[47]),"+f"(d[48]),"+f"(d[49]),"+f"(d[50]),"+f"(d[51]),"+f"(d[52]),"+f"(d[53]),"+f"(d[54]),"+f"(d[55]),"+f"(d[56]),"+f"(d[57]),"+f"(d[58]),"+f"(d[59]),"+f"(d[60]),"+f"(d[61]),"+f"(d[62]),"+f"(d[63])
        : "l"(da), "l"(db), "r"(sd));
}
__device__ __forceinline__ void wgmma_n256_kn(float (&d)[128], uint64_t da, uint64_t db, int sd) {
    asm volatile("{ .reg .pred p; setp.ne.b32 p, %130, 0;\n"
        "wgmma.mma_async.sync.aligned.m64n256k16.f32.bf16.bf16 {%0,%1,%2,%3,%4,%5,%6,%7,%8,%9,%10,%11,%12,%13,%14,%15,%16,%17,%18,%19,%20,%21,%22,%23,%24,%25,%26,%27,%28,%29,%30,%31,%32,%33,%34,%35,%36,%37,%38,%39,%40,%41,%42,%43,%44,%45,%46,%47,%48,%49,%50,%51,%52,%53,%54,%55,%56,%57,%58,%59,%60,%61,%62,%63,%64,%65,%66,%67,%68,%69,%70,%71,%72,%73,%74,%75,%76,%77,%78,%79,%80,%81,%82,%83,%84,%85,%86,%87,%88,%89,%90,%91,%92,%93,%94,%95,%96,%97,%98,%99,%100,%101,%102,%103,%104,%105,%106,%107,%108,%109,%110,%111,%112,%113,%114,%115,%116,%117,%118,%119,%120,%121,%122,%123,%124,%125,%126,%127}, %128, %129, p, 1, 1, 0, 1; }"
        : "+f"(d[0]),"+f"(d[1]),"+f"(d[2]),"+f"(d[3]),"+f"(d[4]),"+f"(d[5]),"+f"(d[6]),"+f"(d[7]),"+f"(d[8]),"+f"(d[9]),"+f"(d[10]),"+f"(d[11]),"+f"(d[12]),"+f"(d[13]),"+f"(d[14]),"+f"(d[15]),"+f"(d[16]),"+f"(d[17]),"+f"(d[18]),"+f"(d[19]),"+f"(d[20]),"+f"(d[21]),"+f"(d[22]),"+f"(d[23]),"+f"(d[24]),"+f"(d[25]),"+f"(d[26]),"+f"(d[27]),"+f"(d[28]),"+f"(d[29]),"+f"(d[30]),"+f"(d[31]),"+f"(d[32]),"+f"(d[33]),"+f"(d[34]),"+f"(d[35]),"+f"(d[36]),"+f"(d[37]),"+f"(d[38]),"+f"(d[39]),"+f"(d[40]),"+f"(d[41]),"+f"(d[42]),"+f"(d[43]),"+f"(d[44]),"+f"(d[45]),"+f"(d[46]),"+f"(d[47]),"+f"(d[48]),"+f"(d[49]),"+f"(d[50]),"+f"(d[51]),"+f"(d[52]),"+f"(d[53]),"+f"(d[54]),"+f"(d[55]),"+f"(d[56]),"+f"(d[57]),"+f"(d[58]),"+f"(d[59]),"+f"(d[60]),"+f"(d[61]),"+f"(d[62]),"+f"(d[63]),"+f"(d[64]),"+f"(d[65]),"+f"(d[66]),"+f"(d[67]),"+f"(d[68]),"+f"(d[69]),"+f"(d[70]),"+f"(d[71]),"+f"(d[72]),"+f"(d[73]),"+f"(d[74]),"+f"(d[75]),"+f"(d[76]),"+f"(d[77]),"+f"(d[78]),"+f"(d[79]),"+f"(d[80]),"+f"(d[81]),"+f"(d[82]),"+f"(d[83]),"+f"(d[84]),"+f"(d[85]),"+f"(d[86]),"+f"(d[87]),"+f"(d[88]),"+f"(d[89]),"+f"(d[90]),"+f"(d[91]),"+f"(d[92]),"+f"(d[93]),"+f"(d[94]),"+f"(d[95]),"+f"(d[96]),"+f"(d[97]),"+f"(d[98]),"+f"(d[99]),"+f"(d[100]),"+f"(d[101]),"+f"(d[102]),"+f"(d[103]),"+f"(d[104]),"+f"(d[105]),"+f"(d[106]),"+f"(d[107]),"+f"(d[108]),"+f"(d[109]),"+f"(d[110]),"+f"(d[111]),"+f"(d[112]),"+f"(d[113]),"+f"(d[114]),"+f"(d[115]),"+f"(d[116]),"+f"(d[117]),"+f"(d[118]),"+f"(d[119]),"+f"(d[120]),"+f"(d[121]),"+f"(d[122]),"+f"(d[123]),"+f"(d[124]),"+f"(d[125]),"+f"(d[126]),"+f"(d[127])
        : "l"(da), "l"(db), "r"(sd));
}
__device__ __forceinline__ void wgmma_n8_mk(float (&d)[4], uint64_t da, uint64_t db, int sd) {
    asm volatile("{ .reg .pred p; setp.ne.b32 p, %6, 0;\n"
        "wgmma.mma_async.sync.aligned.m64n8k16.f32.bf16.bf16 {%0,%1,%2,%3}, %4, %5, p, 1, 1, 1, 0; }"
        : "+f"(d[0]),"+f"(d[1]),"+f"(d[2]),"+f"(d[3])
        : "l"(da), "l"(db), "r"(sd));
}
__device__ __forceinline__ void wgmma_n32_rs(float (&d)[16], const uint32_t (&a)[4], uint64_t db, int sd) {
    asm volatile("{ .reg .pred p; setp.ne.b32 p, %21, 0;\n"
        "wgmma.mma_async.sync.aligned.m64n32k16.f32.bf16.bf16 {%0,%1,%2,%3,%4,%5,%6,%7,%8,%9,%10,%11,%12,%13,%14,%15}, {%16,%17,%18,%19}, %20, p, 1, 1, 0; }"
        : "+f"(d[0]),"+f"(d[1]),"+f"(d[2]),"+f"(d[3]),"+f"(d[4]),"+f"(d[5]),"+f"(d[6]),"+f"(d[7]),"+f"(d[8]),"+f"(d[9]),"+f"(d[10]),"+f"(d[11]),"+f"(d[12]),"+f"(d[13]),"+f"(d[14]),"+f"(d[15])
        : "r"(a[0]), "r"(a[1]), "r"(a[2]), "r"(a[3]), "l"(db), "r"(sd));
}
__device__ __forceinline__ void wgmma_n32_mk(float (&d)[16], uint64_t da, uint64_t db, int sd) {
    asm volatile("{ .reg .pred p; setp.ne.b32 p, %18, 0;\n"
        "wgmma.mma_async.sync.aligned.m64n32k16.f32.bf16.bf16 {%0,%1,%2,%3,%4,%5,%6,%7,%8,%9,%10,%11,%12,%13,%14,%15}, %16, %17, p, 1, 1, 1, 0; }"
        : "+f"(d[0]),"+f"(d[1]),"+f"(d[2]),"+f"(d[3]),"+f"(d[4]),"+f"(d[5]),"+f"(d[6]),"+f"(d[7]),"+f"(d[8]),"+f"(d[9]),"+f"(d[10]),"+f"(d[11]),"+f"(d[12]),"+f"(d[13]),"+f"(d[14]),"+f"(d[15])
        : "l"(da), "l"(db), "r"(sd));
}

constexpr int F1_BN = 224, F1_STAGES = 4;
constexpr int F1_A_BYTES = 128 * 64 * 2, F1_B_BYTES = 64 * F1_BN * 2, F1_STAGE_BYTES = F1_A_BYTES + F1_B_BYTES;
constexpr int F1_STG_PITCH = 240, F1_STG_WARP = 16 * F1_STG_PITCH;
constexpr int F1_SMEM = F1_STAGES * F1_STAGE_BYTES + 8 * F1_STG_WARP + 256 + 1024;
constexpr int F1_TILES = (S_ / 128) * (F_ / F1_BN);

__global__ void __launch_bounds__(384, 1)
ffn1_kernel(const __grid_constant__ CUtensorMap tm_x, const __grid_constant__ CUtensorMap tm_w1,
            const __nv_bfloat16* __restrict__ b1, const __nv_bfloat16* __restrict__ x, const __nv_bfloat16* __restrict__ gate_w,
            const unsigned char* __restrict__ wq, const unsigned char* __restrict__ wk, const unsigned char* __restrict__ wv,
            const unsigned char* __restrict__ wo, const __nv_bfloat16* __restrict__ mem0) {
    extern __shared__ unsigned char smem_raw[];
    const uint32_t sbase = (smem_u32(smem_raw) + 1023) & ~1023u;
    const uint32_t stg = sbase + F1_STAGES * F1_STAGE_BYTES;
    const uint32_t bars = stg + 8 * F1_STG_WARP;
    const int tid = threadIdx.x, warp = tid >> 5, lane = tid & 31;
    if (tid == 0) {
        for (int s = 0; s < F1_STAGES; s++) { mbar_init(bars + s * 8, 1); mbar_init(bars + 64 + s * 8, 8); }
        asm volatile("fence.mbarrier_init.release.cluster;" ::: "memory");
    }
    __syncthreads();
    if (warp >= 8) {
        asm volatile("setmaxnreg.dec.sync.aligned.u32 56;");
        if (warp == 8) {
            if (lane == 0) {
                int it = 0;
                for (int t = blockIdx.x; t < F1_TILES; t += gridDim.x) {
                    const int mt = t & 15, nt = t >> 4;
                    for (int kb = 0; kb < 16; kb++, it++) {
                        const int st = it % F1_STAGES;
                        mbar_wait(bars + 64 + st * 8, ((it / F1_STAGES) & 1) ^ 1);
                        const uint32_t a = sbase + st * F1_STAGE_BYTES;
                        mbar_expect_tx(bars + st * 8, F1_STAGE_BYTES);
                        tma_2d(a, &tm_x, kb * 64, mt * 128, bars + st * 8);
                        tma_3d(a + F1_A_BYTES, &tm_w1, 0, kb * 64, nt * 7, bars + st * 8);
                    }
                }
            }
        } else {
            const int ht = (warp - 9) * 32 + lane, nht = 96;
            uint4* cz = (uint4*)comm_base();
            if (blockIdx.x * nht + ht < 1024) {
                const int r = blockIdx.x * nht + ht;
                const unsigned short* src = (const unsigned short*)mem0 + (r & ~15) + (r & 3) + ((r >> 2) & 1) * 8 + ((r >> 3) & 1) * 4;
                uint32_t w[4];
                #pragma unroll
                for (int e = 0; e < 4; e++) w[e] = (uint32_t)__ldg(src + (2 * e) * D_) | ((uint32_t)__ldg(src + (2 * e + 1) * D_) << 16);
                cz[OFF_MEM0 / 16 + r] = make_uint4(w[0], w[1], w[2], w[3]);
            }
            for (uint32_t i = blockIdx.x * nht + ht; i < OFF_MEM0 / 16; i += gridDim.x * nht) {
                const bool pad = i >= OFF_XP / 16 && i < OFF_MEM / 16 && (i & 4095) >= 3072;
                if (!pad) cz[i] = make_uint4(0, 0, 0, 0);
            }
            for (int r = blockIdx.x * 3 + (warp - 9); r < S_; r += gridDim.x * 3) {
                float acc = 0.f;
                #pragma unroll
                for (int u = 0; u < 4; u++) {
                    const uint4 xv = __ldg((const uint4*)(x + (size_t)r * D_) + u * 32 + lane);
                    const uint4 gv = __ldg((const uint4*)gate_w + u * 32 + lane);
                    acc += bf_lo(xv.x) * bf_lo(gv.x) + bf_hi(xv.x) * bf_hi(gv.x) + bf_lo(xv.y) * bf_lo(gv.y) + bf_hi(xv.y) * bf_hi(gv.y)
                         + bf_lo(xv.z) * bf_lo(gv.z) + bf_hi(xv.z) * bf_hi(gv.z) + bf_lo(xv.w) * bf_lo(gv.w) + bf_hi(xv.w) * bf_hi(gv.w);
                }
                #pragma unroll
                for (int o = 16; o > 0; o >>= 1) acc += __shfl_xor_sync(~0u, acc, o);
                if (lane == 0) g_gate[r] = 1.f / (1.f + __expf(-acc));
            }
            for (int i = blockIdx.x * nht + ht; i < 4 * 2048; i += gridDim.x * nht) {
                const int m = i >> 11;
                const unsigned char* p = (m == 0 ? wq : m == 1 ? wk : m == 2 ? wv : wo) + (size_t)(i & 2047) * 4096;
                asm volatile("cp.async.bulk.prefetch.L2.global [%0], %1;" :: "l"(p), "r"(4096) : "memory");
            }
        }
    } else {
        asm volatile("setmaxnreg.inc.sync.aligned.u32 216;");
        const int wg = warp >> 2;
        int it = 0;
        for (int t = blockIdx.x; t < F1_TILES; t += gridDim.x) {
            const int mt = t & 15, nt = t >> 4;
            float acc[112];
            for (int kb = 0; kb < 16; kb++, it++) {
                const int st = it % F1_STAGES;
                mbar_wait(bars + st * 8, (it / F1_STAGES) & 1);
                const uint32_t a = sbase + st * F1_STAGE_BYTES;
                const uint64_t da = mkdesc(a + wg * 8192, 16, 1024, 1);
                const uint64_t db = mkdesc(a + F1_A_BYTES, 4096, 512, 2);
                WG_FENCE();
                #pragma unroll
                for (int k = 0; k < 4; k++) wgmma_n224_kn(acc, da + k * 2, db + k * 64, (kb | k) != 0);
                WG_COMMIT();
                if (kb > 0) { WG_WAIT(1); if (lane == 0) mbar_arrive(bars + 64 + ((it - 1) % F1_STAGES) * 8); }
            }
            WG_WAIT(0);
            if (lane == 0) mbar_arrive(bars + 64 + ((it - 1) % F1_STAGES) * 8);
            const uint32_t ws = stg + warp * F1_STG_WARP;
            const int row0 = mt * 128 + warp * 16, col0 = nt * F1_BN;
            const int q = lane & 3;
            #pragma unroll
            for (int hf = 0; hf < 2; hf++) {
                #pragma unroll
                for (int jj = 0; jj < 7; jj++) {
                    uint32_t w[4];
                    #pragma unroll
                    for (int e = 0; e < 2; e++) {
                        const int j = hf * 14 + jj * 2 + e;
                        const uint32_t bw = __ldg((const uint32_t*)(b1 + col0 + j * 8 + q * 2));
                        const float bl = bf_lo(bw), bh = bf_hi(bw);
                        float v0 = fmaxf(acc[j * 4 + 0] + bl, 0.f), v1 = fmaxf(acc[j * 4 + 1] + bh, 0.f);
                        float v2 = fmaxf(acc[j * 4 + 2] + bl, 0.f), v3 = fmaxf(acc[j * 4 + 3] + bh, 0.f);
                        w[e * 2 + 0] = pack_bf16(v0 * v0, v1 * v1);
                        w[e * 2 + 1] = pack_bf16(v2 * v2, v3 * v3);
                    }
                    stsm4(ws + ((lane & 7) + ((lane >> 3) & 1) * 8) * F1_STG_PITCH + (jj * 2 + (lane >> 4)) * 16, w[0], w[1], w[2], w[3]);
                }
                __syncwarp();
                #pragma unroll
                for (int u = 0; u < 7; u++) {
                    const int idx = u * 32 + lane, r = idx / 14, c = idx % 14;
                    uint4 v;
                    asm volatile("ld.shared.v4.u32 {%0,%1,%2,%3}, [%4];" : "=r"(v.x), "=r"(v.y), "=r"(v.z), "=r"(v.w) : "r"(ws + r * F1_STG_PITCH + c * 16));
                    *(uint4*)(g_h + (size_t)(row0 + r) * F_ + col0 + hf * 112 + c * 8) = v;
                }
                __syncwarp();
            }
        }
    }
}

constexpr int F3_STAGES = 6;
constexpr int F3_STAGE_BYTES = 32768;
constexpr int F3_STG_PITCH = 272, F3_STG_WARP = 16 * F3_STG_PITCH;
constexpr int F3_SMEM = F3_STAGES * F3_STAGE_BYTES + 256 + 1024;
constexpr int F3_KB1 = F_ / 64, F3_KB = F3_KB1 + HD_ / 64;

__global__ void __launch_bounds__(384, 1)
final_kernel(const __grid_constant__ CUtensorMap tm_h, const __grid_constant__ CUtensorMap tm_w2,
             const __grid_constant__ CUtensorMap tm_ox, const __grid_constant__ CUtensorMap tm_wo,
             const __nv_bfloat16* __restrict__ b2, __nv_bfloat16* __restrict__ out) {
    extern __shared__ unsigned char smem_raw[];
    const uint32_t sbase = (smem_u32(smem_raw) + 1023) & ~1023u;
    const uint32_t bars = sbase + F3_STAGES * F3_STAGE_BYTES;
    const int tid = threadIdx.x, warp = tid >> 5, lane = tid & 31;
    const int mt = blockIdx.x >> 3, nt = blockIdx.x & 7;
    if (tid == 0) {
        for (int s = 0; s < F3_STAGES; s++) { mbar_init(bars + s * 8, 1); mbar_init(bars + 64 + s * 8, 8); }
        asm volatile("fence.mbarrier_init.release.cluster;" ::: "memory");
    }
    __syncthreads();
    if (warp >= 8) {
        asm volatile("setmaxnreg.dec.sync.aligned.u32 40;");
        if (warp == 8 && lane == 0) {
            for (int kb = 0; kb < F3_KB; kb++) {
                const int st = kb % F3_STAGES;
                mbar_wait(bars + 64 + st * 8, ((kb / F3_STAGES) & 1) ^ 1);
                const uint32_t a = sbase + st * F3_STAGE_BYTES;
                mbar_expect_tx(bars + st * 8, F3_STAGE_BYTES);
                if (kb < F3_KB1) {
                    tma_2d(a, &tm_h, kb * 64, mt * 128, bars + st * 8);
                    tma_3d(a + 16384, &tm_w2, 0, kb * 64, nt * 2, bars + st * 8);
                } else {
                    tma_2d(a, &tm_ox, (kb - F3_KB1) * 64, mt * 128, bars + st * 8);
                    tma_3d(a + 16384, &tm_wo, 0, (kb - F3_KB1) * 64, nt * 2, bars + st * 8);
                }
            }
        }
    } else {
        asm volatile("setmaxnreg.inc.sync.aligned.u32 232;");
        const int wg = warp >> 2, q = lane & 3;
        const int row0 = mt * 128 + warp * 16, col0 = nt * 128;
        float acc[64];
        for (int kb = 0; kb < F3_KB; kb++) {
            const int st = kb % F3_STAGES;
            if (kb == F3_KB1) {
                WG_WAIT(0);
                const float s0 = 1.f - g_gate[row0 + (lane >> 2)], s1 = 1.f - g_gate[row0 + 8 + (lane >> 2)];
                #pragma unroll
                for (int j = 0; j < 16; j++) {
                    const uint32_t bw = __ldg((const uint32_t*)(b2 + col0 + j * 8 + q * 2));
                    acc[j * 4 + 0] = (acc[j * 4 + 0] + bf_lo(bw)) * s0; acc[j * 4 + 1] = (acc[j * 4 + 1] + bf_hi(bw)) * s0;
                    acc[j * 4 + 2] = (acc[j * 4 + 2] + bf_lo(bw)) * s1; acc[j * 4 + 3] = (acc[j * 4 + 3] + bf_hi(bw)) * s1;
                }
            }
            mbar_wait(bars + st * 8, (kb / F3_STAGES) & 1);
            const uint32_t a = sbase + st * F3_STAGE_BYTES;
            const uint64_t da = mkdesc(a + wg * 8192, 16, 1024, 1);
            const uint64_t db = mkdesc(a + 16384, 8192, 1024, 1);
            WG_FENCE();
            #pragma unroll
            for (int k = 0; k < 4; k++) wgmma_n128_kn(acc, da + k * 2, db + k * 128, (kb | k) != 0);
            WG_COMMIT();
            if (kb > 0) { WG_WAIT(1); if (lane == 0) mbar_arrive(bars + 64 + ((kb - 1) % F3_STAGES) * 8); }
        }
        WG_WAIT(0);
        bar_sync(1, 256);
        const uint32_t ws = sbase + warp * F3_STG_WARP;
        #pragma unroll
        for (int jj = 0; jj < 8; jj++) {
            stsm4(ws + ((lane & 7) + ((lane >> 3) & 1) * 8) * F3_STG_PITCH + (jj * 2 + (lane >> 4)) * 16,
                  pack_bf16(acc[jj * 8 + 0], acc[jj * 8 + 1]), pack_bf16(acc[jj * 8 + 2], acc[jj * 8 + 3]),
                  pack_bf16(acc[jj * 8 + 4], acc[jj * 8 + 5]), pack_bf16(acc[jj * 8 + 6], acc[jj * 8 + 7]));
        }
        __syncwarp();
        #pragma unroll
        for (int u = 0; u < 8; u++) {
            const int idx = u * 32 + lane, r = idx >> 4, c = idx & 15;
            uint4 v;
            asm volatile("ld.shared.v4.u32 {%0,%1,%2,%3}, [%4];" : "=r"(v.x), "=r"(v.y), "=r"(v.z), "=r"(v.w) : "r"(ws + r * F3_STG_PITCH + c * 16));
            *(uint4*)(out + (size_t)(row0 + r) * D_ + col0 + c * 8) = v;
        }
    }
}

constexpr int R_WO = 0;
constexpr int R_XB = 65536;
constexpr int R_SP = 131072;
constexpr int R_VRED = R_SP;
constexpr int R_SRED = R_SP + 8192;
constexpr int R_MEMT = R_SP + 20480;
constexpr int R_OT = R_MEMT + 8192;
constexpr int R_P = R_OT + 2048;
constexpr int R_VX = R_P + 2048;
constexpr int R_AP = R_VX + 8192;
constexpr int R_XS = R_AP + 8192;
constexpr int R_BAR = R_XS + 36864;
constexpr int R_SEL = R_BAR + 128;
constexpr int R_TAB = R_SEL + 128;
constexpr int R_LT = R_TAB + 512;
constexpr int R_GT = R_LT + 10240;
constexpr int R_SMEM = R_GT + 2048;
#define NAF1 4
constexpr int NAF = 4;
constexpr int POLL_LIMIT = 1 << 21;

__device__ __forceinline__ uint32_t settag(uint32_t w, uint32_t tag) { return (w & ~1u) | tag; }
__device__ __forceinline__ uint32_t chk2(uint32_t a, uint32_t b, uint32_t m) {
    uint32_t r; asm("lop3.b32 %0, %1, %2, %3, 0x42;" : "=r"(r) : "r"(a), "r"(b), "r"(m)); return r;
}
__device__ __forceinline__ uint32_t and3(uint32_t a, uint32_t b, uint32_t c) {
    uint32_t r; asm("lop3.b32 %0, %1, %2, %3, 0x80;" : "=r"(r) : "r"(a), "r"(b), "r"(c)); return r;
}
__device__ __forceinline__ uint2 ldg64(const void* p) {
    uint2 v; asm volatile("{ .reg .b64 t; ld.relaxed.gpu.global.b64 t, [%2]; mov.b64 {%0,%1}, t; }" : "=r"(v.x), "=r"(v.y) : "l"(p) : "memory"); return v;
}
__device__ __forceinline__ uint4 ldg128(const void* p) {
    uint4 v; asm volatile("{ .reg .b64 t, u; ld.relaxed.gpu.global.v2.b64 {t, u}, [%4]; mov.b64 {%0,%1}, t; mov.b64 {%2,%3}, u; }"
                          : "=r"(v.x), "=r"(v.y), "=r"(v.z), "=r"(v.w) : "l"(p) : "memory"); return v;
}
__device__ __forceinline__ void stg64(void* p, uint32_t a, uint32_t b) {
    asm volatile("{ .reg .b64 t; mov.b64 t, {%1,%2}; st.relaxed.gpu.global.b64 [%0], t; }" :: "l"(p), "r"(a), "r"(b) : "memory");
}
__device__ __forceinline__ void stg128(void* p, uint32_t a, uint32_t b, uint32_t c, uint32_t d) {
    asm volatile("{ .reg .b64 t, u; mov.b64 t, {%1,%2}; mov.b64 u, {%3,%4}; st.relaxed.gpu.global.v2.b64 [%0], {t, u}; }"
                 :: "l"(p), "r"(a), "r"(b), "r"(c), "r"(d) : "memory");
}
__device__ __forceinline__ uint32_t lds32(uint32_t a) { uint32_t v; asm volatile("ld.volatile.shared.u32 %0, [%1];" : "=r"(v) : "r"(a) : "memory"); return v; }
__device__ __forceinline__ void lds128(uint32_t (&v)[4], uint32_t a) {
    asm volatile("ld.shared.v4.u32 {%0,%1,%2,%3}, [%4];" : "=r"(v[0]), "=r"(v[1]), "=r"(v[2]), "=r"(v[3]) : "r"(a) : "memory");
}
__device__ __forceinline__ void lds128f(float& a, float& b, float& c, float& d, uint32_t p) {
    asm volatile("ld.shared.v4.f32 {%0,%1,%2,%3}, [%4];" : "=f"(a), "=f"(b), "=f"(c), "=f"(d) : "r"(p) : "memory");
}
__device__ __forceinline__ void lds64f(float& a, float& b, uint32_t p) {
    asm volatile("ld.shared.v2.f32 {%0,%1}, [%2];" : "=f"(a), "=f"(b) : "r"(p) : "memory");
}
__device__ __forceinline__ uint2 lds64(uint32_t a) { uint2 v; asm volatile("ld.volatile.shared.v2.u32 {%0,%1}, [%2];" : "=r"(v.x), "=r"(v.y) : "r"(a) : "memory"); return v; }
__device__ __forceinline__ void sts64(uint32_t p, uint32_t a, uint32_t b) { asm volatile("st.shared.v2.u32 [%0], {%1,%2};" :: "r"(p), "r"(a), "r"(b) : "memory"); }
__device__ __forceinline__ void sts128(uint32_t p, uint32_t a, uint32_t b, uint32_t c, uint32_t d) {
    asm volatile("st.shared.v4.u32 [%0], {%1,%2,%3,%4};" :: "r"(p), "r"(a), "r"(b), "r"(c), "r"(d) : "memory");
}
__device__ __forceinline__ void sts128f(uint32_t p, float a, float b, float c, float d) {
    asm volatile("st.shared.v4.f32 [%0], {%1,%2,%3,%4};" :: "r"(p), "f"(a), "f"(b), "f"(c), "f"(d) : "memory");
}
__device__ __forceinline__ void sts64f(uint32_t p, float a, float b) {
    asm volatile("st.shared.v2.f32 [%0], {%1,%2};" :: "r"(p), "f"(a), "f"(b) : "memory");
}
__device__ __forceinline__ float ex2(float x) { float r; asm("ex2.approx.ftz.f32 %0, %1;" : "=f"(r) : "f"(x)); return r; }
__device__ __forceinline__ float rcp(float x) { float r; asm("rcp.approx.ftz.f32 %0, %1;" : "=f"(r) : "f"(x)); return r; }
template <class T> __device__ __forceinline__ void pin64(T*& p) { asm volatile("" : "+l"(p)); }
__device__ __forceinline__ void pin32(uint32_t& v) { v = __shfl_sync(~0u, v, threadIdx.x & 31); }
template <class T> __device__ __forceinline__ T* pxor(T* p, uint32_t m) { return (T*)((uintptr_t)p ^ (uintptr_t)m); }

template <int N> struct IC { static constexpr int value = N; };
#define POLL_FAIL() (--budget < 0)
#define SCHED_FENCE() do { if (budget == -0x40000000) asm volatile("trap;"); } while (0)
__device__ __forceinline__ void wait_until(uint32_t t0, int d) { while ((int)(clk32() - t0) < d) {} }
#define PT(idx) do {} while (0)

__global__ void __launch_bounds__(256, 1)
recur_kernel(const __grid_constant__ CUtensorMap tm_wq, const __grid_constant__ CUtensorMap tm_wk,
             const __grid_constant__ CUtensorMap tm_wv, const __grid_constant__ CUtensorMap tm_wo,
             const __grid_constant__ CUtensorMap tm_x) {
    extern __shared__ unsigned char smem_raw[];
    constexpr uint32_t sb = 1024;
    if (smem_u32(smem_raw) != sb) { g_err = 9; asm volatile("trap;"); }
    const int tid = threadIdx.x, lane = tid & 31;
    const int warp = __shfl_sync(~0u, tid >> 5, 0);
    const int wg = warp >> 2, w4 = warp & 3;
    const int h = blockIdx.x >> 2, ci = blockIdx.x & 3, th = ci >> 1, kh = ci & 1;
    const uint32_t bar_w = sb + R_BAR;
    unsigned char* const comm = comm_base();

    if (tid == 0) {
        for (int b = 0; b < 10; b++) mbar_init(bar_w + b * 8, 1);
        mbar_init(bar_w + 10 * 8, 8);
        asm volatile("fence.mbarrier_init.release.cluster;" ::: "memory");
        const int col = h * 128 + th * 64, row = kh * 512;
        #pragma unroll
        for (int c = 0; c < 2; c++) {
            mbar_expect_tx(bar_w + (0 + c) * 8, 32768); tma_2d(sb + R_XB + c * 32768, &tm_wq, col, row + c * 256, bar_w + (0 + c) * 8);
            mbar_expect_tx(bar_w + (2 + c) * 8, 32768); tma_2d(sb + R_WO + c * 32768, &tm_wk, col, row + c * 256, bar_w + (2 + c) * 8);
            mbar_expect_tx(bar_w + (4 + c) * 8, 32768); tma_2d(sb + R_SP + c * 32768, &tm_wv, col, row + c * 256, bar_w + (4 + c) * 8);
        }
        sts128(sb + R_SEL + 64, 0u, sb, sb, sb);
    }
    if (warp >= 1 && warp <= 3 && lane == 0) {
        unsigned char* pb = comm + (warp == 1 ? h * 65536 : warp == 2 ? OFF_P1 + blockIdx.x * 16384 : OFF_MEM) + 4032;
        uint32_t best0 = 0xffffffffu, best1 = 0xffffffffu;
        #pragma unroll 1
        for (int r = 0; r < 8; r++) {
            const uint32_t t0 = clk32();
            uint32_t v, t1;
            asm volatile("atom.relaxed.gpu.global.add.u32 %0, [%1], 0;" : "=r"(v) : "l"(pb + (r & 1) * 4096) : "memory");
            asm volatile("{ .reg .pred p; setp.ne.u32 p, %1, 0x7fc17fc3; mov.u32 %0, 0; @p mov.u32 %0, %%clock; }" : "=r"(t1) : "r"(v) : "memory");
            const uint32_t dt = t1 - t0;
            if (r & 1) best1 = min(best1, dt); else best0 = min(best0, dt);
        }
        asm volatile("st.shared.u32 [%0], %1;" :: "r"(sb + R_SEL + (warp - 1) * 4), "r"(best1 < best0 ? 1u : 0u) : "memory");
    }
    __syncthreads();
    if (tid == 0) stg_rlx1(comm + OFF_SELT + blockIdx.x * 4, 4u | lds32(sb + R_SEL) | (lds32(sb + R_SEL + 4) << 1));
    const uint32_t lda = ((lane & 7) + ((lane >> 4) & 1) * 8) * 128 + (uint32_t)(((w4 * 2 + ((lane >> 3) & 1)) ^ (lane & 7)) * 16);
    uint32_t wA[32][4], wV[16][4];
    {
        const uint32_t aA = sb + (wg == 0 ? R_XB : R_WO) + lda;
        mbar_wait(bar_w + (wg * 2 + wg) * 8, 0);
        #pragma unroll
        for (int k = 0; k < 16; k++) ldsm4t(wA[k], aA + wg * 32768 + k * 2048);
        mbar_wait(bar_w + (4 + wg) * 8, 0);
        #pragma unroll
        for (int k = 0; k < 16; k++) ldsm4t(wV[k], sb + R_SP + wg * 32768 + lda + k * 2048);
        mbar_wait(bar_w + (wg * 2 + (wg ^ 1)) * 8, 0);
        #pragma unroll
        for (int k = 0; k < 16; k++) ldsm4t(wA[16 + k], aA + (wg ^ 1) * 32768 + k * 2048);
    }
    __syncthreads();
    if (tid == 0) {
        #pragma unroll
        for (int b = 0; b < 2; b++) {
            mbar_expect_tx(bar_w + (7 + b) * 8, 32768);
            tma_3d(sb + R_XB + b * 32768, &tm_x, 0, b * 32, kh * 8, bar_w + (7 + b) * 8);
        }
        mbar_expect_tx(bar_w + 6 * 8, 65536);
        #pragma unroll
        for (int t = 0; t < 4; t++) tma_2d(sb + R_WO + t * 16384, &tm_wo, ci * 256 + t * 64, h * 128, bar_w + 6 * 8);
    }
    const uint32_t sel_ex = __shfl_sync(~0u, lds32(sb + R_SEL), 0), sel_p1 = __shfl_sync(~0u, lds32(sb + R_SEL + 4), 0),
                   sel_mem = __shfl_sync(~0u, lds32(sb + R_SEL + 8), 0);
    int budget = POLL_LIMIT;
    uint32_t need_ex, sel_red;
    {
        const int c = lane < 4 ? h * 4 + lane : (((lane >> 1) & 1) * 16 + warp * 2 + (lane & 1)) * 4 + ci;
        uint32_t v;
        do { asm volatile("ld.relaxed.gpu.global.u32 %0, [%1];" : "=r"(v) : "l"(comm + OFF_SELT + (c & 127) * 4) : "memory"); }
        while (!__all_sync(~0u, (v & 4u) != 0) && --budget >= 0);
        const uint32_t e1 = __ballot_sync(~0u, v & 1u) & 15u;
        need_ex = (e1 != 15u ? 1u : 0u) | (e1 != 0u ? 2u : 0u);
        sel_red = (__ballot_sync(~0u, v & 2u) >> 4) & 15u;
    }
    {
        const int pw = th * 4 + w4;
        const int msl = kh * 2 + wg;
        const int r0 = (need_ex & 1) ? 0 : 1;
        uint32_t t = 0;
        if (lane == 0) t = h * 65536 + (2 * (pw >> 1) + (r0 ^ ((pw >> 1) & 1))) * 4096 + wg * 1024 + (pw & 1) * 512 + kh * 256;
        if (lane == 1) t = h * 65536 + (2 * (pw >> 1) + (r0 ^ ((pw >> 1) & 1))) * 4096 + 2048 + (pw & 1) * 1024 + kh * 512 + wg * 256;
        if (lane == 2) t = h * 65536 + (2 * (warp >> 1) + (sel_ex ^ ((warp >> 1) & 1))) * 4096;
        if (lane == 3) t = OFF_XP + h * 262144 + (wg ? 16384 + pw * 2048 + kh * 512 : (pw >> 1) * 1024 + kh * 512 + (pw & 1) * 256);
        if (lane == 4) t = OFF_XP + h * 262144 + 32768 + pw * 2048 + wg * 1024 + kh * 512;
        if (lane == 5) t = OFF_P1 + (warp * 8 + ci) * 16384 + h * 64;
        if (lane == 6) t = OFF_P1 + blockIdx.x * 16384 + sel_p1 * 4096 + (warp & 1) * 2048;
        if (lane == 7) t = OFF_MEM + ci * 8192 + h * 128 + (warp & 1) * 32;
        if (lane == 8) t = OFF_MEM + (2 * msl + (sel_mem ^ (msl & 1))) * 4096 + w4 * 512;
        if (lane == 9) t = sb + R_MEMT + wg * 4096;
        if (lane == 10) t = sb + R_MEMT + (wg ^ 1) * 4096;
        if (lane == 11) t = sb + R_SRED + (warp >> 1) * 2816 + (warp & 1) * 64;
        if (lane == 12) t = sb + R_SRED + warp * 352;
        if (lane == 13) t = sb + R_P + warp * 112;
        if (lane == 14) t = sb + R_OT + (warp >> 1) * 512 + (warp & 1) * 8;
        if (lane == 15) t = sb + R_XS + 4096 + (warp >> 1) * 4096 + (warp & 1) * 1024;
        if (lane < 16) asm volatile("st.shared.u32 [%0], %1;" :: "r"(sb + R_TAB + warp * 64 + lane * 4), "r"(t) : "memory");
        __syncwarp();
    }
#define UTAB(i) __shfl_sync(~0u, lds32(sb + R_TAB + warp * 64 + (i) * 4), 0)
#define u_sex UTAB(2)
#define u_sp1 UTAB(6)
#define u_dmem UTAB(7)
#define u_smem UTAB(8)
    const uint32_t u_m0 = sb + R_MEMT + wg * 4096, u_m1 = sb + R_MEMT + (wg ^ 1) * 4096, u_sr = sb + R_SRED + warp * 352,
                   u_pw = sb + R_P + warp * 112, u_ow = sb + R_OT + (warp >> 1) * 512 + (warp & 1) * 8;
    const bool both_ex = need_ex == 3u;
    uint32_t l8 = lane * 8, t16 = tid * 16;
    {
        const uint32_t ld = UTAB(5) + (lane >> 4) * 65536 + ((lane >> 3) & 1) * 2048 + (lane & 7) * 8;
        sts64(sb + R_LT + tid * 8, ld + (((sel_red >> (lane >> 4)) & 1) << 12), ld + (((sel_red >> (2 + (lane >> 4))) & 1) << 12) + 16 * 4 * 16384);
        sts64(sb + R_LT + 2048 + tid * 8, lda + sb + R_WO + wg * 16384, UTAB(15) + lane * 16);
        sts64(sb + R_LT + 4096 + tid * 8, UTAB(0) + lane * 8, UTAB(1) + lane * 8);
        sts64(sb + R_LT + 6144 + tid * 8, UTAB(11) + (lane >> 2) * 352 + (lane & 3) * 8,
              sb + R_MEMT + wg * 4096 + w4 * 512 + ((lane & 19) + ((lane & 4) << 1) + ((lane & 8) >> 1)) * 16);
        sts64(sb + R_LT + 8192 + tid * 8, UTAB(3) + lane * (wg ? 16 : 8), UTAB(4) + lane * 16);
    }
#define LTAB(i) lds64((t16 >> 1) + (sb + R_LT + (i) * 2048))
    #pragma unroll
    for (int e = 0; e < 2; e++) {
        const int i = tid + e * 256;
        asm volatile("st.shared.f32 [%0], %1;" :: "r"(sb + R_GT + i * 4), "f"(g_gate[(i >> 3) * 32 + ci * 8 + (i & 7)]) : "memory");
    }
    pin32(l8); pin32(t16);
#define L16 (l8 * 2)
#define LG (l8 >> 5)
    const float sc2 = 0.08838834764831845f * 1.4426950408889634f;

    float acc[16];
    auto x_issue_v = [&](uint64_t d) {
        WG_FENCE();
        #pragma unroll
        for (int k = 0; k < 16; k++) wgmma_n32_rs(acc, wV[k], d + (k >> 2) * 256 + (k & 3) * 2, k != 0);
        WG_COMMIT();
    };
    auto x_issue_lo = [&](uint64_t d) {
        WG_FENCE();
        #pragma unroll
        for (int k = 0; k < 16; k++) wgmma_n32_rs(acc, wA[k], d + (k >> 2) * 256 + (k & 3) * 2, k != 0);
        WG_COMMIT();
    };
    auto x_issue_hi = [&](uint64_t d) {
        WG_FENCE();
        #pragma unroll
        for (int k = 0; k < 16; k++) wgmma_n32_rs(acc, wA[16 + k], d + (k >> 2) * 256 + (k & 3) * 2, 1);
        WG_COMMIT();
    };
#define SBV() __shfl_sync(~0u, lds32(sb + R_SEL + 68), 0)
#define SBV3() do { sb0 = SBV(); sb1 = __shfl_sync(~0u, lds32(sb + R_SEL + 72), 0); sb2 = __shfl_sync(~0u, lds32(sb + R_SEL + 76), 0); } while (0)
#define XDESC(sbv, bb, half) mkdesc((sbv) + R_XB + (bb) * 32768 + (half) * 16384, 16, 1024, 1)
    auto v_dump = [&]() {
        const uint32_t vr = t16 + (sb + R_VRED);
        sts128(vr, pack_bf16(acc[0], acc[1]), pack_bf16(acc[4], acc[5]), pack_bf16(acc[2], acc[3]), pack_bf16(acc[6], acc[7]));
        sts128(vr + 4096, pack_bf16(acc[8], acc[9]), pack_bf16(acc[12], acc[13]), pack_bf16(acc[10], acc[11]), pack_bf16(acc[14], acc[15]));
    };
    auto v_final = [&](int seg, uint32_t off) {
        const uint32_t xtag = ((seg >> 2) & 1) ^ 1;
        uint32_t a[4], c[4];
        lds128(a, t16 + (sb + R_VRED + wg * 2048)); lds128(c, t16 + (sb + R_VRED + wg * 2048 + 2048));
        stg128((comm + (seg & 3) * 65536) + off, settag(hadd2_bf16(a[0], c[0]), xtag), hadd2_bf16(a[1], c[1]),
               settag(hadd2_bf16(a[2], c[2]), xtag), hadd2_bf16(a[3], c[3]));
    };
    auto a_park = [&](int seg) {
        const uint32_t xtag = ((seg >> 2) & 1) ^ 1;
        uint32_t w[8];
        #pragma unroll
        for (int j = 0; j < 8; j++) w[j] = movm(pack_bf16(acc[2 * j], acc[2 * j + 1]));
        sts128(t16 + (sb + R_AP), settag(w[0], xtag), w[1], settag(w[2], xtag), w[3]);
        sts128(t16 + (sb + R_AP + 4096), settag(w[4], xtag), w[5], settag(w[6], xtag), w[7]);
    };
    auto a_store = [&](int seg, uint32_t off) {
        uint32_t w0[4], w1[4];
        lds128(w0, t16 + (sb + R_AP)); lds128(w1, t16 + (sb + R_AP + 4096));
        unsigned char* d = (comm + (seg & 3) * 65536) + off;
        if (wg) {
            stg128(d, w0[0], w0[1], w0[2], w0[3]);
            stg128(d + 1024, w1[0], w1[1], w1[2], w1[3]);
        } else {
            stg64(d, w0[0], w0[1]); stg64(d + 4096, w0[2], w0[3]); stg64(d + 8192, w1[0], w1[1]); stg64(d + 12288, w1[2], w1[3]);
        }
    };
    auto xs_issue = [&](int seg) {
        const unsigned char* src = comm + (OFF_XP + h * 262144 + (seg & 3) * 65536);
        mbar_expect_tx(bar_w + 9 * 8, 36864);
        bulk_g2s(sb + R_XS, src + ci * 4096, 4096, bar_w + 9 * 8);
        bulk_g2s(sb + R_XS + 4096, src + 16384, 32768, bar_w + 9 * 8);
    };
    auto take3 = [&](int seg, int i0) {
        const uint32_t tm = ((seg >> 2) & 1) ? ~0u : 0u;
        uint32_t a[3][4], c[3][4];
        while (true) {
            uint32_t ok = 1u;
            #pragma unroll
            for (int i = 0; i < 3; i++) { lds128(a[i], L16 + (sb + R_XS + (i0 + i) * 1024)); lds128(c[i], L16 + (sb + R_XS + (i0 + i) * 1024 + 512)); }
            #pragma unroll
            for (int i = 0; i < 3; i++) ok = and3(ok, chk2(a[i][0], c[i][0], tm), chk2(a[i][2], c[i][2], tm));
            if (__all_sync(~0u, ok != 0) || POLL_FAIL()) break;
            #pragma unroll 1
            for (int i = 0; i < 6; i++) {
                const uint32_t o = i0 * 1024 + i * 512;
                const uint4 t = ldg128((comm + (OFF_XP + h * 262144 + (seg & 3) * 65536 + (o < 4096 ? ci * 4096 : 12288) + o)) + L16);
                sts128(L16 + (sb + R_XS + o), t.x, t.y, t.z, t.w);
            }
        }
        #pragma unroll
        for (int i = 0; i < 3; i++)
            sts128(L16 + (i0 + i < 20 ? sb + R_XS + (i0 + i) * 1024 : sb + R_VX + ((i0 + i) & 1) * 4096 + ((i0 + i - 20) >> 1) * 512),
                   hadd2_bf16(a[i][0], c[i][0]), hadd2_bf16(a[i][1], c[i][1]), hadd2_bf16(a[i][2], c[i][2]), hadd2_bf16(a[i][3], c[i][3]));
    };
    auto take_all = [&](int seg) {
        #pragma unroll 1
        for (int r = 0; r < 2; r++) take3(seg, (warp - 2) * 6 + r * 3);
    };

    #pragma unroll 1
    for (int seg = 0; seg < 3; seg++) {
        mbar_wait(bar_w + (7 + (seg & 1)) * 8, (seg >> 1) & 1);
        x_issue_v(XDESC(SBV(), seg & 1, wg)); WG_WAIT(0);
        v_dump();
        x_issue_lo(XDESC(SBV(), seg & 1, wg)); x_issue_hi(XDESC(SBV(), seg & 1, wg ^ 1));
        __syncthreads();
        v_final(seg, LTAB(4).y);
        WG_WAIT(0);
        a_park(seg);
        if (seg < 2) a_store(seg, LTAB(4).x);
        __syncthreads();
        if (tid == 0 && seg < 2) {
            mbar_expect_tx(bar_w + (7 + seg) * 8, 32768);
            tma_3d(sb + R_XB + seg * 32768, &tm_x, 0, (2 + seg) * 32, kh * 8, bar_w + (7 + seg) * 8);
        }
        if (tid == 0 && seg == 1) xs_issue(0);
    }
    mbar_wait(bar_w + 9 * 8, 0);
    if (warp >= 2) take_all(0);
    mbar_wait(bar_w + 6 * 8, 0);
    mbar_wait(bar_w + 8 * 8, 1);
    uint4 mv0, mv1;
    {
        const unsigned char* sm = (comm + (OFF_MEM0 + (kh * 2 + wg) * 4096 + w4 * 512)) + L16;
        mv0 = ldg128(sm); mv1 = ldg128(sm + 2048);
    }
    uint32_t sb0, sb1, sb2;
    SBV3();
    uint32_t a_st = LTAB(3).y;
    for (int s = 0;; s++) {
        const uint32_t tag = ((s >> 1) & 1) ^ 1;
        const uint32_t tm = tag - 1u;
        const int bb = s & 1, seg = s + 3, xb = bb ^ 1;
        asm volatile("" : "+r"(l8), "+r"(t16));
        sts128(a_st, mv0.x, mv0.y, mv0.z, mv0.w); sts128(a_st + 2048, mv1.x, mv1.y, mv1.z, mv1.w);
        const uint2 o_qv = LTAB(2);
        __syncthreads();
        if (EXP_T && warp == 7) {
            if (l8 == 0 && s + 4 < NSEG) {
                mbar_expect_tx(bar_w + (7 + bb) * 8, 32768);
                tma_3d(sb + R_XB + bb * 32768, &tm_x, 0, (s + 4) * 32, kh * 8, bar_w + (7 + bb) * 8);
            }
            __syncwarp();
        }
        PT(1);
        {
            float a0[4] = {0.f, 0.f, 0.f, 0.f}, a1[4] = {0.f, 0.f, 0.f, 0.f}, a2[4] = {0.f, 0.f, 0.f, 0.f}, a3[4] = {0.f, 0.f, 0.f, 0.f};
            float v0[4] = {0.f, 0.f, 0.f, 0.f}, v1[4] = {0.f, 0.f, 0.f, 0.f};
            #pragma unroll
            for (int u = 0; u < 8; u++) {
                uint32_t b0[4], b1[4];
                ldsm4t(b0, L16 + (u_m0 + u * 512)); ldsm4t(b1, L16 + (u_m1 + u * 512));
                const int k = 2 * u;
                mma16816(a0, wA[k][0], wA[k][1], wA[k][2], wA[k][3], b0[0], b0[1]);
                mma16816(v0, wV[k][0], wV[k][1], wV[k][2], wV[k][3], b0[0], b0[1]);
                mma16816(a1, wA[k + 1][0], wA[k + 1][1], wA[k + 1][2], wA[k + 1][3], b0[2], b0[3]);
                mma16816(v1, wV[k + 1][0], wV[k + 1][1], wV[k + 1][2], wV[k + 1][3], b0[2], b0[3]);
                mma16816(a2, wA[16 + k][0], wA[16 + k][1], wA[16 + k][2], wA[16 + k][3], b1[0], b1[1]);
                mma16816(a3, wA[17 + k][0], wA[17 + k][1], wA[17 + k][2], wA[17 + k][3], b1[2], b1[3]);
            }
            const uint32_t w0 = settag(movm(pack_bf16((a0[0] + a1[0]) + (a2[0] + a3[0]), (a0[1] + a1[1]) + (a2[1] + a3[1]))), tag);
            const uint32_t w1 = movm(pack_bf16((a0[2] + a1[2]) + (a2[2] + a3[2]), (a0[3] + a1[3]) + (a2[3] + a3[3])));
            const uint32_t y0 = settag(pack_bf16(v0[0] + v1[0], v0[1] + v1[1]), tag);
            const uint32_t y1 = pack_bf16(v0[2] + v1[2], v0[3] + v1[3]);
            unsigned char* dq = (comm + bb * 32768) + o_qv.x;
            unsigned char* dv = (comm + bb * 32768) + o_qv.y;
            stg64(dq, w0, w1); stg64(dv, y0, y1);
            if (both_ex) { stg64(pxor(dq, 4096), w0, w1); stg64(pxor(dv, 4096), y0, y1); }
        }
        SCHED_FENCE();
        uint32_t t_send = clk32();
        PT(2);
        if (EXP_W) x_issue_v(XDESC(sb0, xb, wg));
        uint2 va[4];
        uint32_t aw2;
        uint32_t af[NAF][4];
        {
            const unsigned char* sx = (comm + (u_sex + bb * 32768)) + l8;
            const unsigned char* sv = sx + (2048 + (warp & 1) * 1024);
            wait_until(t_send, D_EX);
            const bool ev = (warp & 1) == 0;
            uint2 a[8];
            #pragma unroll
            for (int u = 0; u < 4; u++) a[u] = ldg64(sx + u * 256);
            #pragma unroll
            for (int u = 4; u < 8; u++) { a[u].x = ~tm; a[u].y = 0u; }
            if (ev) {
                #pragma unroll
                for (int u = 4; u < 8; u++) a[u] = ldg64(sx + u * 256);
            }
            const uint2 awk = LTAB(1);
            WG_WAIT(0);
            if (EXP_S) v_dump();
            uint32_t kx0[4], kx1[4], qx[4];
            lds128(kx0, awk.y); lds128(kx1, awk.y + 2048);
            { const uint2 q0 = lds64(l8 + (sb + R_XS + (warp >> 1) * 1024)), q1 = lds64(l8 + (sb + R_XS + (warp >> 1) * 1024 + 256));
              qx[0] = q0.x; qx[1] = q0.y; qx[2] = q1.x; qx[3] = q1.y; }
            const uint32_t sr = LTAB(3).x;
            #pragma unroll
            for (int k = 0; k < NAF1; k++) ldsm4t(af[k], awk.x + k * 2048);
            SCHED_FENCE();
            PT(3);
            while (true) {
                const uint32_t ok = and3(and3(chk2(a[0].x, a[1].x, tm), chk2(a[2].x, a[3].x, tm), chk2(a[4].x, a[5].x, tm)), chk2(a[6].x, a[7].x, tm), 1u);
                if (__all_sync(~0u, ok != 0) || POLL_FAIL()) break;
                #pragma unroll
                for (int u = 0; u < 4; u++) a[u] = ldg64(sx + u * 256);
                if (ev) {
                    #pragma unroll
                    for (int u = 4; u < 8; u++) a[u] = ldg64(sx + u * 256);
                }
            }
            aw2 = LTAB(1).x;
            PT(4);
            float sa[3][4];
            #pragma unroll
            for (int j = 0; j < 3; j++) { sa[j][0] = sa[j][1] = sa[j][2] = sa[j][3] = 0.f; }
            #pragma unroll
            for (int ks = 0; ks < 2; ks++) {
                const uint32_t q0 = hadd2_bf16(a[2 * ks].x, a[2 * ks + 1].x), q1 = hadd2_bf16(a[2 * ks].y, a[2 * ks + 1].y);
                mma16816(sa[0], q0, qx[2 * ks], q1, qx[2 * ks + 1], ks ? kx1[0] : kx0[0], ks ? kx1[1] : kx0[1]);
                mma16816(sa[1], q0, qx[2 * ks], q1, qx[2 * ks + 1], ks ? kx1[2] : kx0[2], ks ? kx1[3] : kx0[3]);
                mma16816(sa[2], q0, qx[2 * ks], q1, qx[2 * ks + 1],
                         hadd2_bf16(a[4 + 2 * ks].x, a[5 + 2 * ks].x), hadd2_bf16(a[4 + 2 * ks].y, a[5 + 2 * ks].y));
            }
            sts64f(sr, sa[0][0], sa[0][1]); sts64f(sr + 32, sa[1][0], sa[1][1]);
            sts64f(sr + 160, sa[0][2], sa[0][3]); sts64f(sr + 192, sa[1][2], sa[1][3]);
            if (ev) { sts64f(sr + 128, sa[2][0], sa[2][1]); sts64f(sr + 288, sa[2][2], sa[2][3]); }
            #pragma unroll
            for (int u = 0; u < 4; u++) va[u] = ldg64(sv + u * 256);
        }
        #pragma unroll
        for (int k = NAF1; k < NAF; k++) ldsm4t(af[k], aw2 + (k >> 3) * 32768 + (k & 7) * 2048);
        __syncthreads();
        if (EXP_T && warp == 7) { if (l8 == 0 && s + 1 < NSEG) xs_issue(EXP_S ? s + 1 : 0); __syncwarp(); }
        PT(5);
        {
            float v[4];
            {
                float t[4][4];
                #pragma unroll
                for (int w = 0; w < 4; w++) {
                    t[w][0] = t[w][1] = t[w][2] = t[w][3] = 0.f;
                    asm volatile("{ .reg .pred p; setp.lt.u32 p, %5, 160; @p ld.shared.v4.f32 {%0,%1,%2,%3}, [%4]; }"
                                 : "+f"(t[w][0]), "+f"(t[w][1]), "+f"(t[w][2]), "+f"(t[w][3]) : "r"(L16 + (u_sr + w * 2816)), "r"(l8) : "memory");
                }
                #pragma unroll
                for (int e = 0; e < 4; e++) v[e] = (t[0][e] + t[1][e]) + (t[2][e] + t[3][e]);
            }
            if (EXP_S) { const uint2 o = LTAB(4); v_final(seg, o.y); a_store(seg - 1, o.x); }
            const bool xr = l8 >= 80;
            const int lim = (xr && l8 < 144) ? ci * 8 + warp + 40 - (int)(l8 >> 1) : 64;
            #pragma unroll
            for (int e = 0; e < 4; e++) if (e > lim) v[e] = -1.0e9f / 0.08838834764831845f;
            const float mxl = fmaxf(fmaxf(v[0], v[1]), fmaxf(v[2], v[3]));
            int key = __float_as_int(mxl); key ^= (key >> 31) & 0x7fffffff;
            const int m0 = __reduce_max_sync(~0u, xr ? (int)0x80000000 : key);
            const int m1 = __reduce_max_sync(~0u, (xr && l8 < 160) ? key : (int)0x80000000);
            int mk = xr ? m1 : m0; mk ^= (mk >> 31) & 0x7fffffff;
            const float mb = -__int_as_float(mk) * sc2;
            const uint32_t p0 = pack_bf16(ex2(fmaf(v[0], sc2, mb)), ex2(fmaf(v[1], sc2, mb)));
            const uint32_t p1 = pack_bf16(ex2(fmaf(v[2], sc2, mb)), ex2(fmaf(v[3], sc2, mb)));
            if (l8 < 160) asm volatile("st.shared.v2.u32 [%0], {%1,%2};" :: "r"(l8 + (xr ? 8 * 112 - 80 : 0) + u_pw), "r"(p0), "r"(p1) : "memory");
            uint32_t tm2 = tm; asm volatile("{ .reg .pred p; setp.eq.u32 p, %1, 0x7fc17fc3; @p not.b32 %0, %0; }" : "+r"(tm2) : "r"(p1));
            while (true) {
                if (__all_sync(~0u, and3(chk2(va[0].x, va[1].x, tm2), chk2(va[2].x, va[3].x, tm2), 1u) != 0) || POLL_FAIL()) break;
                tm2 = tm;
                const unsigned char* sv = (comm + (u_sex + bb * 32768 + 2048 + (warp & 1) * 1024)) + l8;
                #pragma unroll
                for (int u = 0; u < 4; u++) va[u] = ldg64(sv + u * 256);
            }
        }
        const uint32_t vm0 = hadd2_bf16(hadd2_bf16(va[0].x, va[1].x), hadd2_bf16(va[2].x, va[3].x));
        const uint32_t vm1 = hadd2_bf16(hadd2_bf16(va[0].y, va[1].y), hadd2_bf16(va[2].y, va[3].y));
        uint32_t vxa[4], vxb[4];
        lds128(vxa, t16 + (sb + R_VX)); lds128(vxb, t16 + (sb + R_VX + 4096));
        __syncthreads();
        PT(6);
        uint32_t ox0, ox1;
        {
            uint32_t p0[4], p1[4], pm[2];
            const uint32_t pa = (l8 & 0x78) * 14 + (sb + R_P);
            ldsm4(p0, pa + ((l8 >> 3) & 16)); ldsm4(p1, pa + 32 + ((l8 >> 3) & 16)); ldsm2(pm, pa + 64);
            float lo[4] = {0.f, 0.f, 0.f, 0.f}, hi[4] = {0.f, 0.f, 0.f, 0.f}, sm[4] = {0.f, 0.f, 0.f, 0.f};
            const uint32_t ones = 0x3f803f80u;
            mma16816(sm, p0[0], p0[1], p0[2], p0[3], ones, ones);
            mma16816(lo, p0[0], p0[1], p0[2], p0[3], vxa[0], vxa[1]);
            mma16816(hi, p0[0], p0[1], p0[2], p0[3], vxa[2], vxa[3]);
            mma16816(sm, p1[0], p1[1], p1[2], p1[3], ones, ones);
            mma16816(lo, p1[0], p1[1], p1[2], p1[3], vxb[0], vxb[1]);
            mma16816(hi, p1[0], p1[1], p1[2], p1[3], vxb[2], vxb[3]);
            mma1688(sm, pm[0], pm[1], ones);
            mma1688(lo, pm[0], pm[1], vm0);
            mma1688(hi, pm[0], pm[1], vm1);
            const float im = rcp(sm[0]), ix = rcp(sm[2]);
            asm volatile("st.shared.v2.u32 [%0], {%1,%2};" :: "r"(L16 + u_ow),
                         "r"(pack_bf16(lo[0] * im, lo[1] * im)), "r"(pack_bf16(hi[0] * im, hi[1] * im)) : "memory");
            const float f = ix * __uint_as_float(lds32(LG * 4 + (sb + R_GT + s * 32)));
            ox0 = pack_bf16(lo[2] * f, lo[3] * f); ox1 = pack_bf16(hi[2] * f, hi[3] * f);
        }
        const uint2 ldp = LTAB(0);
        const uint32_t a_wo = LTAB(1).x;
        __syncthreads();
        PT(7);
        {
            uint32_t ob[4][4];
            #pragma unroll
            for (int w = 0; w < 4; w++) lds128(ob[w], L16 + (sb + R_OT + w * 512));
            unsigned char* dd0 = comm + (ldp.x ^ (bb * 0x3000));
            unsigned char* dd1 = comm + (ldp.y ^ (bb * 0x3000));
            #pragma unroll
            for (int t = 0; t < 2; t++) {
                float c0[4] = {0.f, 0.f, 0.f, 0.f}, c1[4] = {0.f, 0.f, 0.f, 0.f};
                #pragma unroll
                for (int k = 0; k < 8; k++) {
                    const int i = t * 8 + k;
                    if (k & 1) mma16816(c1, af[i % NAF][0], af[i % NAF][1], af[i % NAF][2], af[i % NAF][3], ob[k >> 1][2], ob[k >> 1][3]);
                    else       mma16816(c0, af[i % NAF][0], af[i % NAF][1], af[i % NAF][2], af[i % NAF][3], ob[k >> 1][0], ob[k >> 1][1]);
                    if (i + NAF < 16) ldsm4t(af[i % NAF], a_wo + ((i + NAF) >> 3) * 32768 + ((i + NAF) & 7) * 2048);
                }
                const uint32_t w0 = settag(pack_bf16(c0[0] + c1[0], c0[1] + c1[1]), tag), w1 = pack_bf16(c0[2] + c1[2], c0[3] + c1[3]);
                stg64(t ? dd1 : dd0, w0, w1);
            }
        }
        SCHED_FENCE();
        t_send = clk32();
        PT(8);
        {
            const bool od = l8 & 8;
            const uint32_t t = __shfl_xor_sync(~0u, od ? ox0 : ox1, 1);
            *(uint2*)(g_ox + (size_t)(s * 32 + ci * 8 + LG) * HD_ + h * 128 + warp * 16 + (od ? 8 : 0) + ((l8 >> 2) & 4)) =
                od ? make_uint2(t, ox1) : make_uint2(ox0, t);
        }
        if (s + 1 == NSEG) break;
        if (EXP_W) x_issue_lo(XDESC(sb1, xb, wg));
        PT(9);
        if (warp < 2) {
            const unsigned char* sp = (comm + (u_sp1 ^ (bb * 0x3000))) + ((l8 & 24) * 8 + (l8 >> 5) * 8);
            unsigned char* dm = (comm + (u_dmem + bb * 32768)) + ((l8 & 0x40) * 64 + (l8 & 0x20) * 2 + (l8 & 24));
            uint2 a[8];
            wait_until(t_send, D_P1);
            while (true) {
                #pragma unroll
                for (int u = 0; u < 8; u++) a[u] = ldg64(sp + u * 256);
                const uint32_t ok = and3(and3(chk2(a[0].x, a[1].x, tm), chk2(a[2].x, a[3].x, tm), chk2(a[4].x, a[5].x, tm)), chk2(a[6].x, a[7].x, tm), 1u);
                if (__all_sync(~0u, ok != 0) || POLL_FAIL()) break;
            }
            PT(10);
            const uint32_t e0m = (l8 & 32) ? 0u : 0x00003f80u, e1m = e0m << 16, e2m = e0m ^ 0x00003f80u, e3m = e2m << 16;
            float r[4][4];
            #pragma unroll
            for (int e = 0; e < 4; e++) { r[e][0] = r[e][1] = r[e][2] = r[e][3] = 0.f; }
            #pragma unroll
            for (int u = 0; u < 8; u++) mma16816(r[u & 3], e0m, e1m, e2m, e3m, a[u].x, a[u].y);
            const uint32_t w0 = pack_bf16((r[0][0] + r[1][0]) + (r[2][0] + r[3][0]), (r[0][2] + r[1][2]) + (r[2][2] + r[3][2]));
            const uint32_t w1 = pack_bf16((r[0][1] + r[1][1]) + (r[2][1] + r[3][1]), (r[0][3] + r[1][3]) + (r[2][3] + r[3][3]));
            if (l8 < 128) stg64(dm, settag(w0, tag), w1);
        } else {
            if (EXP_T) mbar_wait(bar_w + 9 * 8, (s + 1) & 1);
            if (EXP_K) take_all(s + 1);
            if (EXP_T && s + 4 < NSEG) mbar_wait(bar_w + (7 + bb) * 8, ((s + 4) >> 1) & 1);
        }
        __syncthreads();
        t_send = clk32();
        PT(11);
        if (EXP_W) x_issue_hi(XDESC(sb2, xb, wg ^ 1));
        {
            const unsigned char* sm = (comm + (u_smem + bb * 32768)) + L16;
            wait_until(t_send, D_MEM);
            mv0 = ldg128(sm); mv1 = ldg128(sm + 2048);
            SBV3();
            a_st = LTAB(3).y;
            WG_WAIT(0);
            if (EXP_S) a_park(seg);
            SCHED_FENCE();
            PT(12);
            while (true) {
                if (__all_sync(~0u, and3(chk2(mv0.x, mv0.z, tm), chk2(mv1.x, mv1.z, tm), 1u) != 0) || POLL_FAIL()) break;
                mv0 = ldg128(sm); mv1 = ldg128(sm + 2048);
            }
        }
        PT(0);
    }
    if (budget < 0) g_err = 2;
}

typedef CUresult (*EncodeFn)(CUtensorMap*, CUtensorMapDataType, cuuint32_t, void*, const cuuint64_t*, const cuuint64_t*,
                             const cuuint32_t*, const cuuint32_t*, CUtensorMapInterleave, CUtensorMapSwizzle,
                             CUtensorMapL2promotion, CUtensorMapFloatOOBfill);

void make_2d(EncodeFn enc, CUtensorMap* m, const void* p, uint64_t rows, uint64_t cols, uint32_t box_c, uint32_t box_r) {
    cuuint64_t dims[2] = {cols, rows}; cuuint64_t str[1] = {cols * 2};
    cuuint32_t box[2] = {box_c, box_r}, es[2] = {1, 1};
    enc(m, CU_TENSOR_MAP_DATA_TYPE_BFLOAT16, 2, (void*)p, dims, str, box, es, CU_TENSOR_MAP_INTERLEAVE_NONE,
        CU_TENSOR_MAP_SWIZZLE_128B, CU_TENSOR_MAP_L2_PROMOTION_L2_256B, CU_TENSOR_MAP_FLOAT_OOB_FILL_NONE);
}
void make_3d(EncodeFn enc, CUtensorMap* m, const void* p, uint64_t rows, uint64_t cols, uint32_t inner, uint32_t box_r, uint32_t groups) {
    cuuint64_t dims[3] = {inner, rows, cols / inner}; cuuint64_t str[2] = {cols * 2, (cuuint64_t)inner * 2};
    cuuint32_t box[3] = {inner, box_r, groups}, es[3] = {1, 1, 1};
    enc(m, CU_TENSOR_MAP_DATA_TYPE_BFLOAT16, 3, (void*)p, dims, str, box, es, CU_TENSOR_MAP_INTERLEAVE_NONE,
        inner == 64 ? CU_TENSOR_MAP_SWIZZLE_128B : CU_TENSOR_MAP_SWIZZLE_64B, CU_TENSOR_MAP_L2_PROMOTION_L2_256B,
        CU_TENSOR_MAP_FLOAT_OOB_FILL_NONE);
}

}

extern "C" void kernel_launch(void* const* d_in, const int* in_sizes, int n_in, void* d_out, int out_size) {
    (void)in_sizes; (void)n_in; (void)out_size;
    const __nv_bfloat16* x = (const __nv_bfloat16*)d_in[0];
    const __nv_bfloat16* mem0 = (const __nv_bfloat16*)d_in[1];
    const __nv_bfloat16* wq = (const __nv_bfloat16*)d_in[2];
    const __nv_bfloat16* wk = (const __nv_bfloat16*)d_in[3];
    const __nv_bfloat16* wv = (const __nv_bfloat16*)d_in[4];
    const __nv_bfloat16* wo = (const __nv_bfloat16*)d_in[5];
    const __nv_bfloat16* w1 = (const __nv_bfloat16*)d_in[8];
    const __nv_bfloat16* b1 = (const __nv_bfloat16*)d_in[9];
    const __nv_bfloat16* w2 = (const __nv_bfloat16*)d_in[10];
    const __nv_bfloat16* b2 = (const __nv_bfloat16*)d_in[11];
    const __nv_bfloat16* gw = (const __nv_bfloat16*)d_in[12];
    __nv_bfloat16* out = (__nv_bfloat16*)d_out;

    void* fn = nullptr;
    cudaDriverEntryPointQueryResult qr;
    cudaGetDriverEntryPoint("cuTensorMapEncodeTiled", &fn, cudaEnableDefault, &qr);
    EncodeFn enc = (EncodeFn)fn;
    void *ph = nullptr, *pox = nullptr;
    cudaGetSymbolAddress(&ph, g_h);
    cudaGetSymbolAddress(&pox, g_ox);

    CUtensorMap tm_x128, tm_w1, tm_h, tm_w2, tm_ox, tm_wo_b, tm_wq, tm_wk, tm_wv, tm_wo_a, tm_x32;
    make_2d(enc, &tm_x128, x, S_, D_, 64, 128);
    make_3d(enc, &tm_w1, w1, D_, F_, 32, 64, 7);
    make_2d(enc, &tm_h, ph, S_, F_, 64, 128);
    make_3d(enc, &tm_w2, w2, F_, D_, 64, 64, 2);
    make_2d(enc, &tm_ox, pox, S_, HD_, 64, 128);
    make_3d(enc, &tm_wo_b, wo, HD_, D_, 64, 64, 2);
    make_2d(enc, &tm_wq, wq, D_, HD_, 64, 256);
    make_2d(enc, &tm_wk, wk, D_, HD_, 64, 256);
    make_2d(enc, &tm_wv, wv, D_, HD_, 64, 256);
    make_2d(enc, &tm_wo_a, wo, HD_, D_, 64, 128);
    make_3d(enc, &tm_x32, x, S_, D_, 64, 32, 8);

    cudaFuncSetAttribute(ffn1_kernel, cudaFuncAttributeMaxDynamicSharedMemorySize, F1_SMEM);
    cudaFuncSetAttribute(recur_kernel, cudaFuncAttributeMaxDynamicSharedMemorySize, R_SMEM);
    cudaFuncSetAttribute(final_kernel, cudaFuncAttributeMaxDynamicSharedMemorySize, F3_SMEM);

    cudaStream_t st = cudaStreamPerThread;
    ffn1_kernel<<<132, 384, F1_SMEM, st>>>(tm_x128, tm_w1, b1, x, gw, (const unsigned char*)wq, (const unsigned char*)wk,
                                           (const unsigned char*)wv, (const unsigned char*)wo, mem0);
    recur_kernel<<<128, 256, R_SMEM, st>>>(tm_wq, tm_wk, tm_wv, tm_wo_a, tm_x32);
    final_kernel<<<128, 384, F3_SMEM, st>>>(tm_h, tm_w2, tm_ox, tm_wo_b, b2, out);
}
```

```cpp
#include <cuda_runtime.h>
#include <cuda_bf16.h>
#include <cuda.h>
#include <stdint.h>

#define PROF 0
#define EXP_W 1
#define EXP_T 1
#define EXP_S 1
#define EXP_K 1
#define STPOS 0
#define XSPLIT 0
#define FLAGPOS 0
#define PF_ON 1
#define PF_DELAY 6000
#define PF_STEP 5000
#define F1SW 128
#define PF0_ON 1
#define F1ROT 0
#define L2P CU_TENSOR_MAP_L2_PROMOTION_L2_256B
#define HELP_ON 1
#define TLINE 0
#define PF_NS 400
#define K_SYM 0
#define K_PHI 0
#define K_SOFT 0
#define K_VCHK 0
#define K_XS 1
#define K_VF3 0
#define XV1 16
#define WOFENCE 0
#define K_KXE 0
#define K_P2 0
#define D_P2 170
#define K_OXL 0
#define RW 2
#define XH1 16
#define PFW 0
#define PDL 1
#define KSPLIT 23
#define PF_T0 80000
#define NPROBE 4
#define SKIPW 0
#define ROLES 1
#define MEMFLIP 1u
#define K_MS 0
#define D_MS 130
#define K_R2 0
#define K_WK 1
#define K_DN 0
#define K_PV 0
#define WCH 1
#define XSPOS 0
#define K_SPEC 0
#define K_NB 0
#define K_EXP 1
#define RARE(c) __builtin_expect(!!(c), 0)
#define XPB 12288
#define NOADD 0
#define WOCUT 16
#define GCUT 8
#define NA0 16
#define NA1 24
#define K_G2 1
#define K_VD 1
#define T_HOLD 4000
#define PFMODE 0
#define PF_T2 15000
#define K_NEAR 1
#define PACE 2
#define XTMA 0
#define D_EX 250
#define D_P1 450
#define D_MEM 240
#define PROFM 0xffff
#define PROFA 0xfff

namespace {

constexpr int S_ = 2048, D_ = 1024, H_ = 32, DH_ = 128, HD_ = 4096, F_ = 3584, NSEG = 64;

constexpr uint32_t OFF_P1 = 32u * 32768u;
constexpr uint32_t OFF_MEM = OFF_P1 + 136u * 16384u;
constexpr uint32_t OFF_PROBE = OFF_MEM + 65536u;
constexpr uint32_t OFF_SELT = OFF_PROBE + 8192u;
constexpr uint32_t OFF_FLAG = OFF_SELT + 1024u;
constexpr uint32_t OFF_HCNT = OFF_FLAG + 16384u;
constexpr uint32_t OFF_XP = OFF_HCNT + 2048u + 4096u;
constexpr uint32_t COMM_BYTES = OFF_XP + 32u * 8u * 12288u;

__device__ __align__(1024) unsigned char g_comm_raw[COMM_BYTES + 131072];
__device__ __align__(1024) __nv_bfloat16 g_h[(size_t)S_ * F_];
__device__ __align__(1024) __nv_bfloat16 g_ox[(size_t)S_ * HD_];
__device__ __align__(1024) uint4 g_xch[128 * 8 * 256];
__device__ float g_gate[S_];
__device__ int g_err;
#define TL(k, i) do {} while (0)

__device__ __forceinline__ uint32_t smem_u32(const void* p) { return (uint32_t)__cvta_generic_to_shared(p); }
__device__ __forceinline__ void mbar_init(uint32_t bar, uint32_t cnt) { asm volatile("mbarrier.init.shared::cta.b64 [%0], %1;" :: "r"(bar), "r"(cnt) : "memory"); }
__device__ __forceinline__ void mbar_expect_tx(uint32_t bar, uint32_t bytes) { asm volatile("mbarrier.arrive.expect_tx.shared::cta.b64 _, [%0], %1;" :: "r"(bar), "r"(bytes) : "memory"); }
__device__ __forceinline__ void mbar_arrive(uint32_t bar) { asm volatile("mbarrier.arrive.shared::cta.b64 _, [%0];" :: "r"(bar) : "memory"); }
__device__ __forceinline__ bool mbar_try(uint32_t bar, uint32_t parity) {
    uint32_t ok;
    asm volatile("{ .reg .pred p; mbarrier.try_wait.parity.shared::cta.b64 p, [%1], %2; selp.u32 %0, 1, 0, p; }" : "=r"(ok) : "r"(bar), "r"(parity) : "memory");
    return ok != 0;
}
__device__ __forceinline__ void mbar_wait(uint32_t bar, uint32_t parity) {
    int guard = 0;
    while (!mbar_try(bar, parity)) { if (++guard > (1 << 20)) { g_err = 1; break; } }
}
__device__ __forceinline__ void tma_2d(uint32_t dst, const CUtensorMap* map, int c0, int c1, uint32_t bar) {
    asm volatile("cp.async.bulk.tensor.2d.shared::cluster.global.mbarrier::complete_tx::bytes [%0], [%1, {%3, %4}], [%2];"
                 :: "r"(dst), "l"(map), "r"(bar), "r"(c0), "r"(c1) : "memory");
}
__device__ __forceinline__ void tma_3d(uint32_t dst, const CUtensorMap* map, int c0, int c1, int c2, uint32_t bar) {
    asm volatile("cp.async.bulk.tensor.3d.shared::cluster.global.mbarrier::complete_tx::bytes [%0], [%1, {%3, %4, %5}], [%2];"
                 :: "r"(dst), "l"(map), "r"(bar), "r"(c0), "r"(c1), "r"(c2) : "memory");
}
__device__ __forceinline__ void tma_pf_2d(const CUtensorMap* map, int c0, int c1) {
    asm volatile("cp.async.bulk.prefetch.tensor.2d.L2.global [%0, {%1, %2}];" :: "l"(map), "r"(c0), "r"(c1) : "memory");
}
__device__ __forceinline__ void tma_2d_mc(uint32_t dst, const CUtensorMap* map, int c0, int c1, uint32_t bar) {
    asm volatile("cp.async.bulk.tensor.2d.shared::cluster.global.mbarrier::complete_tx::bytes.multicast::cluster [%0], [%1, {%3, %4}], [%2], %5;"
                 :: "r"(dst), "l"(map), "r"(bar), "r"(c0), "r"(c1), "h"((unsigned short)3) : "memory");
}
__device__ __forceinline__ void tma_3d_mc(uint32_t dst, const CUtensorMap* map, int c0, int c1, int c2, uint32_t bar) {
    asm volatile("cp.async.bulk.tensor.3d.shared::cluster.global.mbarrier::complete_tx::bytes.multicast::cluster [%0], [%1, {%3, %4, %5}], [%2], %6;"
                 :: "r"(dst), "l"(map), "r"(bar), "r"(c0), "r"(c1), "r"(c2), "h"((unsigned short)3) : "memory");
}
__device__ __forceinline__ void mbar_arrive_cluster(uint32_t bar) {
    asm volatile("mbarrier.arrive.shared::cluster.b64 _, [%0];" :: "r"(bar) : "memory");
}
__device__ __forceinline__ void cluster_sync() { asm volatile("barrier.cluster.arrive.aligned;\nbarrier.cluster.wait.aligned;" ::: "memory"); }
__device__ __forceinline__ void bulk_g2s(uint32_t dst, const void* src, uint32_t bytes, uint32_t bar) {
    asm volatile("cp.async.bulk.shared::cluster.global.mbarrier::complete_tx::bytes [%0], [%1], %2, [%3];"
                 :: "r"(dst), "l"(src), "r"(bytes), "r"(bar) : "memory");
}
__device__ __forceinline__ void bulk_s2g(void* dst, uint32_t src, uint32_t bytes) {
    asm volatile("cp.async.bulk.global.shared::cta.bulk_group [%0], [%1], %2;" :: "l"(dst), "r"(src), "r"(bytes) : "memory");
    asm volatile("cp.async.bulk.commit_group;" ::: "memory");
}
__device__ __forceinline__ void bulk_add_s2g(void* dst, uint32_t src, uint32_t bytes) {
    asm volatile("cp.reduce.async.bulk.global.shared::cta.bulk_group.add.noftz.bf16 [%0], [%1], %2;" :: "l"(dst), "r"(src), "r"(bytes) : "memory");
    asm volatile("cp.async.bulk.commit_group;" ::: "memory");
}
__device__ __forceinline__ void bulk_wait_all() { asm volatile("cp.async.bulk.wait_group 0;" ::: "memory"); }
__device__ __forceinline__ void stg_rel1(void* p, uint32_t v) { asm volatile("st.release.gpu.global.u32 [%0], %1;" :: "l"(p), "r"(v) : "memory"); }
__device__ __forceinline__ void bulk_wait_read() { asm volatile("cp.async.bulk.wait_group.read 0;" ::: "memory"); }
__device__ __forceinline__ bool elect_one() {
    uint32_t p;
    asm volatile("{ .reg .b32 rx; .reg .pred px; elect.sync rx|px, 0xffffffff; selp.u32 %0, 1, 0, px; }" : "=r"(p));
    return p != 0;
}
__device__ __forceinline__ uint64_t mkdesc(uint32_t addr, uint32_t lbo, uint32_t sbo, uint32_t swz) {
    return (uint64_t)((addr & 0x3FFFF) >> 4) | ((uint64_t)(lbo >> 4) << 16) | ((uint64_t)(sbo >> 4) << 32) | ((uint64_t)swz << 62);
}
#define WG_FENCE()   asm volatile("wgmma.fence.sync.aligned;" ::: "memory")
#define WG_COMMIT()  asm volatile("wgmma.commit_group.sync.aligned;" ::: "memory")
#define WG_WAIT(n)   asm volatile("wgmma.wait_group.sync.aligned %0;" :: "n"(n) : "memory")
__device__ __forceinline__ void bar_sync(int id, int n) { asm volatile("bar.sync %0, %1;" :: "r"(id), "r"(n) : "memory"); }
__device__ __forceinline__ void bar_arrive(int id, int n) { asm volatile("bar.arrive %0, %1;" :: "r"(id), "r"(n) : "memory"); }
__device__ __forceinline__ void fence_async_smem() { asm volatile("fence.proxy.async.shared::cta;" ::: "memory"); }
__device__ __forceinline__ uint32_t pack_bf16(float lo, float hi) {
    uint32_t r; asm("cvt.rn.bf16x2.f32 %0, %1, %2;" : "=r"(r) : "f"(hi), "f"(lo)); return r;
}
__device__ __forceinline__ uint32_t hadd2_bf16(uint32_t a, uint32_t b) {
    uint32_t r; asm("add.rn.bf16x2 %0, %1, %2;" : "=r"(r) : "r"(a), "r"(b)); return r;
}
__device__ __forceinline__ float bf_lo(uint32_t w) { return __uint_as_float(w << 16); }
__device__ __forceinline__ float bf_hi(uint32_t w) { return __uint_as_float(w & 0xffff0000u); }
__device__ __forceinline__ uint32_t movm(uint32_t a) {
    uint32_t d; asm volatile("movmatrix.sync.aligned.m8n8.trans.b16 %0, %1;" : "=r"(d) : "r"(a)); return d;
}
__device__ __forceinline__ void ldsm4(uint32_t (&r)[4], uint32_t addr) {
    asm volatile("ldmatrix.sync.aligned.m8n8.x4.shared.b16 {%0,%1,%2,%3}, [%4];" : "=r"(r[0]), "=r"(r[1]), "=r"(r[2]), "=r"(r[3]) : "r"(addr) : "memory");
}
__device__ __forceinline__ void ldsm4t(uint32_t (&r)[4], uint32_t addr) {
    asm volatile("ldmatrix.sync.aligned.m8n8.x4.trans.shared.b16 {%0,%1,%2,%3}, [%4];" : "=r"(r[0]), "=r"(r[1]), "=r"(r[2]), "=r"(r[3]) : "r"(addr) : "memory");
}
__device__ __forceinline__ void ldsm2(uint32_t (&r)[2], uint32_t addr) {
    asm volatile("ldmatrix.sync.aligned.m8n8.x2.shared.b16 {%0,%1}, [%2];" : "=r"(r[0]), "=r"(r[1]) : "r"(addr) : "memory");
}
__device__ __forceinline__ void stsm4(uint32_t addr, uint32_t a, uint32_t b, uint32_t c, uint32_t d) {
    asm volatile("stmatrix.sync.aligned.m8n8.x4.shared.b16 [%0], {%1,%2,%3,%4};" :: "r"(addr), "r"(a), "r"(b), "r"(c), "r"(d) : "memory");
}
__device__ __forceinline__ void mma16816(float (&d)[4], uint32_t a0, uint32_t a1, uint32_t a2, uint32_t a3, uint32_t b0, uint32_t b1) {
    asm volatile("mma.sync.aligned.m16n8k16.row.col.f32.bf16.bf16.f32 {%0,%1,%2,%3}, {%4,%5,%6,%7}, {%8,%9}, {%0,%1,%2,%3};"
                 : "+f"(d[0]), "+f"(d[1]), "+f"(d[2]), "+f"(d[3]) : "r"(a0), "r"(a1), "r"(a2), "r"(a3), "r"(b0), "r"(b1));
}
__device__ __forceinline__ void mma1688(float (&d)[4], uint32_t a0, uint32_t a1, uint32_t b0) {
    asm volatile("mma.sync.aligned.m16n8k8.row.col.f32.bf16.bf16.f32 {%0,%1,%2,%3}, {%4,%5}, {%6}, {%0,%1,%2,%3};"
                 : "+f"(d[0]), "+f"(d[1]), "+f"(d[2]), "+f"(d[3]) : "r"(a0), "r"(a1), "r"(b0));
}
__device__ __forceinline__ uint4 ldg_rlx4(const void* p) {
    uint4 v; asm volatile("ld.relaxed.gpu.global.v4.u32 {%0,%1,%2,%3}, [%4];" : "=r"(v.x), "=r"(v.y), "=r"(v.z), "=r"(v.w) : "l"(p) : "memory"); return v;
}
__device__ __forceinline__ uint2 ldg_rlx2(const void* p) {
    uint2 v; asm volatile("ld.relaxed.gpu.global.v2.u32 {%0,%1}, [%2];" : "=r"(v.x), "=r"(v.y) : "l"(p) : "memory"); return v;
}
__device__ __forceinline__ void stg_rlx4(void* p, uint32_t a, uint32_t b, uint32_t c, uint32_t d) {
    asm volatile("st.relaxed.gpu.global.v4.u32 [%0], {%1,%2,%3,%4};" :: "l"(p), "r"(a), "r"(b), "r"(c), "r"(d) : "memory");
}
__device__ __forceinline__ void stg_rlx2(void* p, uint32_t a, uint32_t b) {
    asm volatile("st.relaxed.gpu.global.v2.u32 [%0], {%1,%2};" :: "l"(p), "r"(a), "r"(b) : "memory");
}
__device__ __forceinline__ void stg_rlx1(void* p, uint32_t a) {
    asm volatile("st.relaxed.gpu.global.u32 [%0], %1;" :: "l"(p), "r"(a) : "memory");
}
__device__ __forceinline__ uint32_t ldg_acq1(const void* p) {
    uint32_t v; asm volatile("ld.acquire.gpu.global.u32 %0, [%1];" : "=r"(v) : "l"(p) : "memory"); return v;
}
__device__ __forceinline__ void red_rel_add(void* p, uint32_t v) {
    asm volatile("red.release.gpu.global.add.u32 [%0], %1;" :: "l"(p), "r"(v) : "memory");
}
__device__ __forceinline__ uint32_t clk32() { uint32_t c; asm volatile("mov.u32 %0, %%clock;" : "=r"(c) :: "memory"); return c; }
__device__ __forceinline__ unsigned char* comm_base() {
    return (unsigned char*)(((uintptr_t)g_comm_raw + 131071) & ~(uintptr_t)131071);
}

template <int N> struct IC { static constexpr int value = N; };

__device__ __forceinline__ void wgmma_n224_kn(float (&d)[112], uint64_t da, uint64_t db, int sd) {
    asm volatile("{ .reg .pred p; setp.ne.b32 p, %114, 0;\n"
        "wgmma.mma_async.sync.aligned.m64n224k16.f32.bf16.bf16 {%0,%1,%2,%3,%4,%5,%6,%7,%8,%9,%10,%11,%12,%13,%14,%15,%16,%17,%18,%19,%20,%21,%22,%23,%24,%25,%26,%27,%28,%29,%30,%31,%32,%33,%34,%35,%36,%37,%38,%39,%40,%41,%42,%43,%44,%45,%46,%47,%48,%49,%50,%51,%52,%53,%54,%55,%56,%57,%58,%59,%60,%61,%62,%63,%64,%65,%66,%67,%68,%69,%70,%71,%72,%73,%74,%75,%76,%77,%78,%79,%80,%81,%82,%83,%84,%85,%86,%87,%88,%89,%90,%91,%92,%93,%94,%95,%96,%97,%98,%99,%100,%101,%102,%103,%104,%105,%106,%107,%108,%109,%110,%111}, %112, %113, p, 1, 1, 0, 1; }"
        : "+f"(d[0]),"+f"(d[1]),"+f"(d[2]),"+f"(d[3]),"+f"(d[4]),"+f"(d[5]),"+f"(d[6]),"+f"(d[7]),"+f"(d[8]),"+f"(d[9]),"+f"(d[10]),"+f"(d[11]),"+f"(d[12]),"+f"(d[13]),"+f"(d[14]),"+f"(d[15]),"+f"(d[16]),"+f"(d[17]),"+f"(d[18]),"+f"(d[19]),"+f"(d[20]),"+f"(d[21]),"+f"(d[22]),"+f"(d[23]),"+f"(d[24]),"+f"(d[25]),"+f"(d[26]),"+f"(d[27]),"+f"(d[28]),"+f"(d[29]),"+f"(d[30]),"+f"(d[31]),"+f"(d[32]),"+f"(d[33]),"+f"(d[34]),"+f"(d[35]),"+f"(d[36]),"+f"(d[37]),"+f"(d[38]),"+f"(d[39]),"+f"(d[40]),"+f"(d[41]),"+f"(d[42]),"+f"(d[43]),"+f"(d[44]),"+f"(d[45]),"+f"(d[46]),"+f"(d[47]),"+f"(d[48]),"+f"(d[49]),"+f"(d[50]),"+f"(d[51]),"+f"(d[52]),"+f"(d[53]),"+f"(d[54]),"+f"(d[55]),"+f"(d[56]),"+f"(d[57]),"+f"(d[58]),"+f"(d[59]),"+f"(d[60]),"+f"(d[61]),"+f"(d[62]),"+f"(d[63]),"+f"(d[64]),"+f"(d[65]),"+f"(d[66]),"+f"(d[67]),"+f"(d[68]),"+f"(d[69]),"+f"(d[70]),"+f"(d[71]),"+f"(d[72]),"+f"(d[73]),"+f"(d[74]),"+f"(d[75]),"+f"(d[76]),"+f"(d[77]),"+f"(d[78]),"+f"(d[79]),"+f"(d[80]),"+f"(d[81]),"+f"(d[82]),"+f"(d[83]),"+f"(d[84]),"+f"(d[85]),"+f"(d[86]),"+f"(d[87]),"+f"(d[88]),"+f"(d[89]),"+f"(d[90]),"+f"(d[91]),"+f"(d[92]),"+f"(d[93]),"+f"(d[94]),"+f"(d[95]),"+f"(d[96]),"+f"(d[97]),"+f"(d[98]),"+f"(d[99]),"+f"(d[100]),"+f"(d[101]),"+f"(d[102]),"+f"(d[103]),"+f"(d[104]),"+f"(d[105]),"+f"(d[106]),"+f"(d[107]),"+f"(d[108]),"+f"(d[109]),"+f"(d[110]),"+f"(d[111])
        : "l"(da), "l"(db), "r"(sd));
}
__device__ __forceinline__ void wgmma_n128_kn(float (&d)[64], uint64_t da, uint64_t db, int sd) {
    asm volatile("{ .reg .pred p; setp.ne.b32 p, %66, 0;\n"
        "wgmma.mma_async.sync.aligned.m64n128k16.f32.bf16.bf16 {%0,%1,%2,%3,%4,%5,%6,%7,%8,%9,%10,%11,%12,%13,%14,%15,%16,%17,%18,%19,%20,%21,%22,%23,%24,%25,%26,%27,%28,%29,%30,%31,%32,%33,%34,%35,%36,%37,%38,%39,%40,%41,%42,%43,%44,%45,%46,%47,%48,%49,%50,%51,%52,%53,%54,%55,%56,%57,%58,%59,%60,%61,%62,%63}, %64, %65, p, 1, 1, 0, 1; }"
        : "+f"(d[0]),"+f"(d[1]),"+f"(d[2]),"+f"(d[3]),"+f"(d[4]),"+f"(d[5]),"+f"(d[6]),"+f"(d[7]),"+f"(d[8]),"+f"(d[9]),"+f"(d[10]),"+f"(d[11]),"+f"(d[12]),"+f"(d[13]),"+f"(d[14]),"+f"(d[15]),"+f"(d[16]),"+f"(d[17]),"+f"(d[18]),"+f"(d[19]),"+f"(d[20]),"+f"(d[21]),"+f"(d[22]),"+f"(d[23]),"+f"(d[24]),"+f"(d[25]),"+f"(d[26]),"+f"(d[27]),"+f"(d[28]),"+f"(d[29]),"+f"(d[30]),"+f"(d[31]),"+f"(d[32]),"+f"(d[33]),"+f"(d[34]),"+f"(d[35]),"+f"(d[36]),"+f"(d[37]),"+f"(d[38]),"+f"(d[39]),"+f"(d[40]),"+f"(d[41]),"+f"(d[42]),"+f"(d[43]),"+f"(d[44]),"+f"(d[45]),"+f"(d[46]),"+f"(d[47]),"+f"(d[48]),"+f"(d[49]),"+f"(d[50]),"+f"(d[51]),"+f"(d[52]),"+f"(d[53]),"+f"(d[54]),"+f"(d[55]),"+f"(d[56]),"+f"(d[57]),"+f"(d[58]),"+f"(d[59]),"+f"(d[60]),"+f"(d[61]),"+f"(d[62]),"+f"(d[63])
        : "l"(da), "l"(db), "r"(sd));
}
__device__ __forceinline__ void wgmma_n256_kn(float (&d)[128], uint64_t da, uint64_t db, int sd) {
    asm volatile("{ .reg .pred p; setp.ne.b32 p, %130, 0;\n"
        "wgmma.mma_async.sync.aligned.m64n256k16.f32.bf16.bf16 {%0,%1,%2,%3,%4,%5,%6,%7,%8,%9,%10,%11,%12,%13,%14,%15,%16,%17,%18,%19,%20,%21,%22,%23,%24,%25,%26,%27,%28,%29,%30,%31,%32,%33,%34,%35,%36,%37,%38,%39,%40,%41,%42,%43,%44,%45,%46,%47,%48,%49,%50,%51,%52,%53,%54,%55,%56,%57,%58,%59,%60,%61,%62,%63,%64,%65,%66,%67,%68,%69,%70,%71,%72,%73,%74,%75,%76,%77,%78,%79,%80,%81,%82,%83,%84,%85,%86,%87,%88,%89,%90,%91,%92,%93,%94,%95,%96,%97,%98,%99,%100,%101,%102,%103,%104,%105,%106,%107,%108,%109,%110,%111,%112,%113,%114,%115,%116,%117,%118,%119,%120,%121,%122,%123,%124,%125,%126,%127}, %128, %129, p, 1, 1, 0, 1; }"
        : "+f"(d[0]),"+f"(d[1]),"+f"(d[2]),"+f"(d[3]),"+f"(d[4]),"+f"(d[5]),"+f"(d[6]),"+f"(d[7]),"+f"(d[8]),"+f"(d[9]),"+f"(d[10]),"+f"(d[11]),"+f"(d[12]),"+f"(d[13]),"+f"(d[14]),"+f"(d[15]),"+f"(d[16]),"+f"(d[17]),"+f"(d[18]),"+f"(d[19]),"+f"(d[20]),"+f"(d[21]),"+f"(d[22]),"+f"(d[23]),"+f"(d[24]),"+f"(d[25]),"+f"(d[26]),"+f"(d[27]),"+f"(d[28]),"+f"(d[29]),"+f"(d[30]),"+f"(d[31]),"+f"(d[32]),"+f"(d[33]),"+f"(d[34]),"+f"(d[35]),"+f"(d[36]),"+f"(d[37]),"+f"(d[38]),"+f"(d[39]),"+f"(d[40]),"+f"(d[41]),"+f"(d[42]),"+f"(d[43]),"+f"(d[44]),"+f"(d[45]),"+f"(d[46]),"+f"(d[47]),"+f"(d[48]),"+f"(d[49]),"+f"(d[50]),"+f"(d[51]),"+f"(d[52]),"+f"(d[53]),"+f"(d[54]),"+f"(d[55]),"+f"(d[56]),"+f"(d[57]),"+f"(d[58]),"+f"(d[59]),"+f"(d[60]),"+f"(d[61]),"+f"(d[62]),"+f"(d[63]),"+f"(d[64]),"+f"(d[65]),"+f"(d[66]),"+f"(d[67]),"+f"(d[68]),"+f"(d[69]),"+f"(d[70]),"+f"(d[71]),"+f"(d[72]),"+f"(d[73]),"+f"(d[74]),"+f"(d[75]),"+f"(d[76]),"+f"(d[77]),"+f"(d[78]),"+f"(d[79]),"+f"(d[80]),"+f"(d[81]),"+f"(d[82]),"+f"(d[83]),"+f"(d[84]),"+f"(d[85]),"+f"(d[86]),"+f"(d[87]),"+f"(d[88]),"+f"(d[89]),"+f"(d[90]),"+f"(d[91]),"+f"(d[92]),"+f"(d[93]),"+f"(d[94]),"+f"(d[95]),"+f"(d[96]),"+f"(d[97]),"+f"(d[98]),"+f"(d[99]),"+f"(d[100]),"+f"(d[101]),"+f"(d[102]),"+f"(d[103]),"+f"(d[104]),"+f"(d[105]),"+f"(d[106]),"+f"(d[107]),"+f"(d[108]),"+f"(d[109]),"+f"(d[110]),"+f"(d[111]),"+f"(d[112]),"+f"(d[113]),"+f"(d[114]),"+f"(d[115]),"+f"(d[116]),"+f"(d[117]),"+f"(d[118]),"+f"(d[119]),"+f"(d[120]),"+f"(d[121]),"+f"(d[122]),"+f"(d[123]),"+f"(d[124]),"+f"(d[125]),"+f"(d[126]),"+f"(d[127])
        : "l"(da), "l"(db), "r"(sd));
}
__device__ __forceinline__ void wgmma_n8_mk(float (&d)[4], uint64_t da, uint64_t db, int sd) {
    asm volatile("{ .reg .pred p; setp.ne.b32 p, %6, 0;\n"
        "wgmma.mma_async.sync.aligned.m64n8k16.f32.bf16.bf16 {%0,%1,%2,%3}, %4, %5, p, 1, 1, 1, 0; }"
        : "+f"(d[0]),"+f"(d[1]),"+f"(d[2]),"+f"(d[3])
        : "l"(da), "l"(db), "r"(sd));
}
__device__ __forceinline__ void wgmma_n32_rs(float (&d)[16], const uint32_t (&a)[4], uint64_t db, int sd) {
    asm volatile("{ .reg .pred p; setp.ne.b32 p, %21, 0;\n"
        "wgmma.mma_async.sync.aligned.m64n32k16.f32.bf16.bf16 {%0,%1,%2,%3,%4,%5,%6,%7,%8,%9,%10,%11,%12,%13,%14,%15}, {%16,%17,%18,%19}, %20, p, 1, 1, 0; }"
        : "+f"(d[0]),"+f"(d[1]),"+f"(d[2]),"+f"(d[3]),"+f"(d[4]),"+f"(d[5]),"+f"(d[6]),"+f"(d[7]),"+f"(d[8]),"+f"(d[9]),"+f"(d[10]),"+f"(d[11]),"+f"(d[12]),"+f"(d[13]),"+f"(d[14]),"+f"(d[15])
        : "r"(a[0]), "r"(a[1]), "r"(a[2]), "r"(a[3]), "l"(db), "r"(sd));
}
__device__ __forceinline__ void wgmma_n32_mk(float (&d)[16], uint64_t da, uint64_t db, int sd) {
    asm volatile("{ .reg .pred p; setp.ne.b32 p, %18, 0;\n"
        "wgmma.mma_async.sync.aligned.m64n32k16.f32.bf16.bf16 {%0,%1,%2,%3,%4,%5,%6,%7,%8,%9,%10,%11,%12,%13,%14,%15}, %16, %17, p, 1, 1, 1, 0; }"
        : "+f"(d[0]),"+f"(d[1]),"+f"(d[2]),"+f"(d[3]),"+f"(d[4]),"+f"(d[5]),"+f"(d[6]),"+f"(d[7]),"+f"(d[8]),"+f"(d[9]),"+f"(d[10]),"+f"(d[11]),"+f"(d[12]),"+f"(d[13]),"+f"(d[14]),"+f"(d[15])
        : "l"(da), "l"(db), "r"(sd));
}

#define GRID_WAIT() asm volatile("griddepcontrol.wait;" ::: "memory")
constexpr int G_STAGES = 4, G_A_BYTES = 16384, G_STAGE_BYTES = 49152;
constexpr int F1_BN = 224, F1_TILES = (S_ / 128) * (F_ / F1_BN);
constexpr int F1_STG_PITCH = 240, G_STG_PITCH = 272, G_STG_WARP = 16 * G_STG_PITCH;
constexpr int G_SMEM = G_STAGES * G_STAGE_BYTES + 8 * G_STG_WARP + 256;
constexpr int G_KF = F_ / 128;
constexpr int G_KA0 = KSPLIT;
static_assert(G_SMEM <= 232448, "smem");

__global__ void __cluster_dims__(2, 1, 1) __launch_bounds__(384, 1)
dense_kernel(const __grid_constant__ CUtensorMap tm_x, const __grid_constant__ CUtensorMap tm_w1,
             const __grid_constant__ CUtensorMap tm_h, const __grid_constant__ CUtensorMap tm_w2,
             const __grid_constant__ CUtensorMap tm_ox, const __grid_constant__ CUtensorMap tm_wo,
             const __nv_bfloat16* __restrict__ b1, const __nv_bfloat16* __restrict__ b2, __nv_bfloat16* __restrict__ out,
             const unsigned char* __restrict__ w1p, const unsigned char* __restrict__ w2p, const unsigned char* __restrict__ wop) {
    extern __shared__ __align__(1024) unsigned char smem_raw[];
    const uint32_t sbase = smem_u32(smem_raw);
    if (sbase & 1023u) { g_err = 8; asm volatile("trap;"); }
    const uint32_t stg = sbase + G_STAGES * G_STAGE_BYTES;
    const uint32_t bars = stg + 8 * G_STG_WARP;
    const int tid = threadIdx.x, warp = tid >> 5, lane = tid & 31;
    const int cr = blockIdx.x & 1;
    const bool early = blockIdx.x < 4;
    const int c = (int)blockIdx.x - 4;
    const int rk = (c >> 6) & 1, mt2 = ((c >> 3) & 7) * 2 + cr, nt2 = (c >> 1) & 3;
    const int np = early ? 16 : 2 - rk;
    const int p0 = early ? 96 + (blockIdx.x >> 1) * 16 : c >> 1, pstep = early ? 1 : 64;
    const int ka = rk ? 64 - G_KA0 : G_KA0, ka0 = rk ? G_KA0 : 0;
    unsigned int* const hcnt = (unsigned int*)(comm_base() + OFF_HCNT);
    TL(2, 0);
    if (tid == 256) {
        asm volatile("prefetch.tensormap [%0];" :: "l"(&tm_x) : "memory");
        asm volatile("prefetch.tensormap [%0];" :: "l"(&tm_w1) : "memory");
    }
    if (tid == 0) {
        for (int s = 0; s < G_STAGES; s++) { mbar_init(bars + s * 8, 1); mbar_init(bars + 64 + s * 8, 16); }
        asm volatile("fence.mbarrier_init.release.cluster;" ::: "memory");
    }
    cluster_sync();
    if (warp >= 8) {
        asm volatile("setmaxnreg.dec.sync.aligned.u32 40;");
        if (warp == 8) {
            if (lane == 0) {
                int it = 0;
                for (int i = 0; i < np; i++) {
                    const int p = p0 + i * pstep, mt = (p & 7) * 2 + cr, nt = p >> 3;
                    for (int kb = 0; kb < 16; kb++, it++) {
                        const int st = it % G_STAGES;
                        if (PACE && it == PACE) mbar_wait(bars, 0);
                        mbar_wait(bars + 64 + st * 8, ((it / G_STAGES) & 1) ^ 1);
                        const uint32_t a = sbase + st * G_STAGE_BYTES;
                        mbar_expect_tx(bars + st * 8, G_STAGE_BYTES);
                        tma_2d(a, &tm_x, kb * 64, mt * 128, bars + st * 8);
                        #pragma unroll
                        for (int j = 0; j < 2; j++) tma_2d_mc(a + G_A_BYTES + (cr * 2 + j) * 8192, &tm_w1, nt * F1_BN + (cr * 2 + j) * 64, kb * 64, bars + st * 8);
                    }
                }
                if (!early) {
                    GRID_WAIT();
                    for (int kb = 0; kb < ka + G_KF; kb++, it++) {
                        const int st = it % G_STAGES;
                        if (kb == ka) {
                            int guard = 0;
                            while (ldg_acq1(hcnt + mt2 * 32) < 128u) { if (++guard > (1 << 22)) { g_err = 7; break; } }
                            asm volatile("fence.proxy.async.global;" ::: "memory");
                        }
                        mbar_wait(bars + 64 + st * 8, ((it / G_STAGES) & 1) ^ 1);
                        const uint32_t a = sbase + st * G_STAGE_BYTES;
                        mbar_expect_tx(bars + st * 8, G_STAGE_BYTES);
                        if (kb < ka) {
                            const int k0 = (ka0 + kb) * 64;
                            tma_2d(a, &tm_ox, k0, mt2 * 128, bars + st * 8);
                            tma_3d_mc(a + G_A_BYTES + cr * 16384, &tm_wo, 0, k0, nt2 * 4 + cr * 2, bars + st * 8);
                        } else {
                            const int k0 = (rk * G_KF + kb - ka) * 64;
                            tma_2d(a, &tm_h, k0, mt2 * 128, bars + st * 8);
                            tma_3d_mc(a + G_A_BYTES + cr * 16384, &tm_w2, 0, k0, nt2 * 4 + cr * 2, bars + st * 8);
                        }
                    }
                }
            }
        } else if (warp == 9) {
            for (int i = 0; i < np; i++) {
                bar_sync(2, 288);
                if (lane == 0) red_rel_add(hcnt + (((p0 + i * pstep) & 7) * 2 + cr) * 32, 8);
                __syncwarp();
            }
        } else if (early) {
            if (lane == 0) {
                __nanosleep(PF_T0);
                #pragma unroll 1
                for (int i = blockIdx.x * 2 + warp - 10; i < 512 + 448; i += 8) {
                    const unsigned char* p = (i < 512 ? (PFMODE ? wop : w2p) : w1p - (size_t)512 * 16384) + (size_t)i * 16384;
                    if (!PFMODE && i >= 448 && i < 512) continue;
                    asm volatile("cp.async.bulk.prefetch.L2.global [%0], %1;" :: "l"(p), "r"(16384) : "memory");
                    __nanosleep(PF_NS);
                }
            }
        } else if (warp == 10) {
            if (PFMODE && lane < 7) {
                __nanosleep(PF_T2);
                asm volatile("cp.async.bulk.prefetch.L2.global [%0], %1;" :: "l"(w2p + (size_t)(c * 7 + lane) * 8192), "r"(8192) : "memory");
            }
        } else if (blockIdx.x == 4) {
            GRID_WAIT();
            uint4* cz = (uint4*)(comm_base() + OFF_SELT);
            for (uint32_t i = lane; i < (OFF_HCNT - OFF_SELT) / 16; i += 32) cz[i] = make_uint4(0, 0, 0, 0);
        }
    } else {
        asm volatile("setmaxnreg.inc.sync.aligned.u32 232;");
        const int wg = warp >> 2, q = lane & 3;
        const uint32_t ws = stg + warp * G_STG_WARP;
        uint32_t ebar;
        asm volatile("mapa.shared::cluster.u32 %0, %1, %2;" : "=r"(ebar) : "r"(bars + 64), "r"(lane & 1));
        int it = 0;
        uint32_t hp[56];
        #pragma unroll
        for (int j = 0; j < 56; j++) hp[j] = 0u;
        __nv_bfloat16* hdst = nullptr;
        auto stage = [&](auto half) {
            constexpr int HF = decltype(half)::value;
            __syncwarp();
            #pragma unroll
            for (int jj = 0; jj < 7; jj++)
                stsm4(ws + (lane & 15) * F1_STG_PITCH + (jj * 2 + (lane >> 4)) * 16, hp[HF * 28 + jj * 4], hp[HF * 28 + jj * 4 + 1],
                      hp[HF * 28 + jj * 4 + 2], hp[HF * 28 + jj * 4 + 3]);
            __syncwarp();
        };
        auto store4 = [&](int hf, int r0) {
            int l = lane;
            asm volatile("" : "+r"(l));
            if ((l & 15) < 14) {
                const uint32_t src = ws + (r0 + (l >> 4)) * F1_STG_PITCH + (l & 15) * 16;
                __nv_bfloat16* d = hdst + (size_t)(r0 + (l >> 4)) * F_ + hf * 112 + (l & 15) * 8;
                uint4 v[4];
                #pragma unroll
                for (int u = 0; u < 4; u++)
                    asm volatile("ld.shared.v4.u32 {%0,%1,%2,%3}, [%4];" : "=r"(v[u].x), "=r"(v[u].y), "=r"(v[u].z), "=r"(v[u].w) : "r"(src + u * 2 * F1_STG_PITCH) : "memory");
                #pragma unroll
                for (int u = 0; u < 4; u++) *(uint4*)(d + (size_t)u * 2 * F_) = v[u];
            }
        };
        auto drain = [&](int kb) {
            if (kb < 12) {
                if (kb == 0) stage(IC<0>());
                if (kb == 3) stage(IC<1>());
                if (kb == 1 || kb == 2 || kb == 4 || kb == 5) store4(kb >> 2, (kb == 2 || kb == 5) ? 8 : 0);
                if (kb == 6) {
                    asm volatile("fence.proxy.async.global;" ::: "memory");
                    bar_arrive(2, 288);
                }
            }
        };
        for (int i = 0; i < np; i++) {
            const int p = p0 + i * pstep, mt = (p & 7) * 2 + cr, nt = p >> 3;
            const int row0 = mt * 128 + warp * 16, col0 = nt * F1_BN;
            float acc[112];
            for (int kb = 0; kb < 16; kb++, it++) {
                const int st = it % G_STAGES;
                mbar_wait(bars + st * 8, (it / G_STAGES) & 1);
                if (it == 0) TL(2, 1);
                const uint32_t a = sbase + st * G_STAGE_BYTES;
                const uint64_t da = mkdesc(a + wg * 8192, 16, 1024, 1);
                const uint64_t db = mkdesc(a + G_A_BYTES, 8192, 1024, 1);
                WG_FENCE();
                #pragma unroll
                for (int k = 0; k < 4; k++) wgmma_n224_kn(acc, da + k * 2, db + k * 128, (kb | k) != 0);
                WG_COMMIT();
                if (kb > 0) { WG_WAIT(1); if (lane < 2) mbar_arrive_cluster(ebar + ((it - 1) % G_STAGES) * 8); }
                if (i > 0) drain(kb);
                if (kb == 13) {
                    #pragma unroll
                    for (int j = 0; j < 28; j++) hp[2 * j] = __ldg((const uint32_t*)(b1 + col0 + j * 8 + q * 2));
                    hp[1] = __float_as_uint(g_gate[row0 + (lane >> 2)]); hp[3] = __float_as_uint(g_gate[row0 + 8 + (lane >> 2)]);
                }
            }
            const float s0 = 1.f - __uint_as_float(hp[1]), s1 = 1.f - __uint_as_float(hp[3]);
            WG_WAIT(0);
            if (lane < 2) mbar_arrive_cluster(ebar + ((it - 1) % G_STAGES) * 8);
            TL(2, it == 16 ? 2 : 4);
            #pragma unroll
            for (int j = 0; j < 28; j++) {
                const float bl = bf_lo(hp[2 * j]), bh = bf_hi(hp[2 * j]);
                const float v0 = fmaxf(acc[j * 4 + 0] + bl, 0.f), v1 = fmaxf(acc[j * 4 + 1] + bh, 0.f);
                const float v2 = fmaxf(acc[j * 4 + 2] + bl, 0.f), v3 = fmaxf(acc[j * 4 + 3] + bh, 0.f);
                hp[2 * j] = pack_bf16(v0 * v0 * s0, v1 * v1 * s0);
                hp[2 * j + 1] = pack_bf16(v2 * v2 * s1, v3 * v3 * s1);
            }
            hdst = g_h + (size_t)row0 * F_ + col0;
            TL(2, it == 16 ? 3 : 5);
        }
        if (early) { for (int kb = 0; kb < 12; kb++) drain(kb); }
        if (!early) {
            const int row0 = mt2 * 128 + warp * 16, col0 = nt2 * 256 + rk * 128;
            float acc[128];
            for (int kb = 0; kb < ka + G_KF; kb++, it++) {
                const int st = it % G_STAGES;
                if (kb == ka) {
                    const float g0 = g_gate[row0 + (lane >> 2)], g1 = g_gate[row0 + 8 + (lane >> 2)];
                    WG_WAIT(0);
                    #pragma unroll
                    for (int j = 0; j < 32; j++) { acc[j * 4] *= g0; acc[j * 4 + 1] *= g0; acc[j * 4 + 2] *= g1; acc[j * 4 + 3] *= g1; }
                    TL(2, 6);
                }
                mbar_wait(bars + st * 8, (it / G_STAGES) & 1);
                const uint32_t a = sbase + st * G_STAGE_BYTES;
                const uint64_t da = mkdesc(a + wg * 8192, 16, 1024, 1);
                const uint64_t db = mkdesc(a + G_A_BYTES, 8192, 1024, 1);
                WG_FENCE();
                #pragma unroll
                for (int k = 0; k < 4; k++) wgmma_n256_kn(acc, da + k * 2, db + k * 128, (kb | k) != 0);
                WG_COMMIT();
                if (kb > 0) { WG_WAIT(1); if (lane < 2) mbar_arrive_cluster(ebar + ((it - 1) % G_STAGES) * 8); }
                drain(kb);
            }
            uint32_t bw[16];
            #pragma unroll
            for (int j = 0; j < 16; j++) bw[j] = __ldg((const uint32_t*)(b2 + col0 + j * 8 + q * 2));
            const float s0 = 1.f - g_gate[row0 + (lane >> 2)], s1 = 1.f - g_gate[row0 + 8 + (lane >> 2)];
            WG_WAIT(0);
            TL(2, 7);
            {
                uint4* dst = g_xch + ((size_t)c * 8 + warp) * 256 + lane;
                if (rk) {
                    #pragma unroll
                    for (int j = 0; j < 8; j++)
                        dst[j * 32] = make_uint4(pack_bf16(acc[8 * j], acc[8 * j + 1]), pack_bf16(acc[8 * j + 2], acc[8 * j + 3]),
                                                 pack_bf16(acc[8 * j + 4], acc[8 * j + 5]), pack_bf16(acc[8 * j + 6], acc[8 * j + 7]));
                    #pragma unroll
                    for (int j = 0; j < 64; j++) acc[j] = acc[64 + j];
                } else {
                    #pragma unroll
                    for (int j = 0; j < 8; j++)
                        dst[j * 32] = make_uint4(pack_bf16(acc[64 + 8 * j], acc[65 + 8 * j]), pack_bf16(acc[66 + 8 * j], acc[67 + 8 * j]),
                                                 pack_bf16(acc[68 + 8 * j], acc[69 + 8 * j]), pack_bf16(acc[70 + 8 * j], acc[71 + 8 * j]));
                }
                __syncwarp();
                if (lane == 0) {
                    stg_rel1(hcnt + 512 + c * 8 + warp, 1u);
                    int guard = 0;
                    while (ldg_acq1(hcnt + 512 + (c ^ 64) * 8 + warp) == 0u) { if (++guard > (1 << 22)) { g_err = 6; break; } }
                }
                __syncwarp();
            }
            TL(2, 8);
            uint4 pv[8];
            #pragma unroll
            for (int j = 0; j < 8; j++) pv[j] = __ldcg(g_xch + ((size_t)(c ^ 64) * 8 + warp) * 256 + j * 32 + lane);
            #pragma unroll
            for (int jj = 0; jj < 8; jj++) {
                uint32_t w[4];
                #pragma unroll
                for (int e = 0; e < 2; e++) {
                    const int j = jj * 2 + e;
                    const uint32_t o0 = e ? pv[jj].z : pv[jj].x, o1 = e ? pv[jj].w : pv[jj].y;
                    const float bl = bf_lo(bw[j]), bh = bf_hi(bw[j]);
                    w[e * 2 + 0] = pack_bf16(fmaf(bl, s0, acc[4 * j] + bf_lo(o0)), fmaf(bh, s0, acc[4 * j + 1] + bf_hi(o0)));
                    w[e * 2 + 1] = pack_bf16(fmaf(bl, s1, acc[4 * j + 2] + bf_lo(o1)), fmaf(bh, s1, acc[4 * j + 3] + bf_hi(o1)));
                }
                stsm4(ws + (lane & 15) * G_STG_PITCH + (jj * 2 + (lane >> 4)) * 16, w[0], w[1], w[2], w[3]);
            }
            __syncwarp();
            #pragma unroll
            for (int u = 0; u < 8; u++) {
                const int idx = u * 32 + lane, r = idx >> 4, c = idx & 15;
                uint4 v;
                asm volatile("ld.shared.v4.u32 {%0,%1,%2,%3}, [%4];" : "=r"(v.x), "=r"(v.y), "=r"(v.z), "=r"(v.w) : "r"(ws + r * G_STG_PITCH + c * 16));
                *(uint4*)(out + (size_t)(row0 + r) * D_ + col0 + c * 8) = v;
            }
            TL(2, 9);
        }
        cluster_sync();
    }
}

constexpr int R_WO = 0;
constexpr int R_XB = 65536;
constexpr int R_SP = 131072;
constexpr int R_VRED = R_SP;
constexpr int R_SRED = R_SP + 8192;
constexpr int R_MEMT = R_SP + 20480;
constexpr int R_OT = R_MEMT + 8192;
constexpr int R_P = R_OT + 2048;
constexpr int R_AP = R_P + 2048;
constexpr int R_XS = R_AP + 12288;
constexpr int R_LT = R_XS + 36864;
static_assert(R_LT + 10240 <= R_SP + 98304, "smem map");
constexpr int R_BAR = R_SP + 98304;
constexpr int R_SEL = R_BAR + 128;
constexpr int R_TAB = R_SEL + 128;
constexpr int R_PROF = R_TAB + 512;
constexpr int R_SMEM = R_PROF + 512;
#define NAF1 2
#define NAF2 4
#define NAFX 7
constexpr int NAF = NAFX;
static_assert(R_SMEM <= 232448, "smem");
constexpr int POLL_LIMIT = 1 << 21;

__device__ __forceinline__ uint32_t settag(uint32_t w, uint32_t tag) { return (w & ~1u) | tag; }
__device__ __forceinline__ float pretag(float v, uint32_t radd) {
    return K_NEAR ? __uint_as_float((__float_as_uint(v) + radd) & 0xfffe0000u) : v;
}
__device__ __forceinline__ uint32_t chk2(uint32_t a, uint32_t b, uint32_t m) {
    uint32_t r; asm("lop3.b32 %0, %1, %2, %3, 0x42;" : "=r"(r) : "r"(a), "r"(b), "r"(m)); return r;
}
__device__ __forceinline__ uint32_t and3(uint32_t a, uint32_t b, uint32_t c) {
    uint32_t r; asm("lop3.b32 %0, %1, %2, %3, 0x80;" : "=r"(r) : "r"(a), "r"(b), "r"(c)); return r;
}
__device__ __forceinline__ uint2 ldg64(const void* p) {
    uint2 v; asm volatile("{ .reg .b64 t; ld.relaxed.gpu.global.b64 t, [%2]; mov.b64 {%0,%1}, t; }" : "=r"(v.x), "=r"(v.y) : "l"(p) : "memory"); return v;
}
__device__ __forceinline__ void cpa16(uint32_t dst, const void* src) {
    asm volatile("cp.async.cg.shared.global [%0], [%1], 16;" :: "r"(dst), "l"(src) : "memory");
}
__device__ __forceinline__ void cpa_commit() { asm volatile("cp.async.commit_group;" ::: "memory"); }
#define CPA_WAIT(n) asm volatile("cp.async.wait_group %0;" :: "n"(n) : "memory")
__device__ __forceinline__ uint4 ldg128(const void* p) {
    uint4 v; asm volatile("{ .reg .b64 t, u; ld.relaxed.gpu.global.v2.b64 {t, u}, [%4]; mov.b64 {%0,%1}, t; mov.b64 {%2,%3}, u; }"
                          : "=r"(v.x), "=r"(v.y), "=r"(v.z), "=r"(v.w) : "l"(p) : "memory"); return v;
}
__device__ __forceinline__ void stg64(void* p, uint32_t a, uint32_t b) {
    asm volatile("{ .reg .b64 t; mov.b64 t, {%1,%2}; st.relaxed.gpu.global.b64 [%0], t; }" :: "l"(p), "r"(a), "r"(b) : "memory");
}
__device__ __forceinline__ void stg128(void* p, uint32_t a, uint32_t b, uint32_t c, uint32_t d) {
    asm volatile("{ .reg .b64 t, u; mov.b64 t, {%1,%2}; mov.b64 u, {%3,%4}; st.relaxed.gpu.global.v2.b64 [%0], {t, u}; }"
                 :: "l"(p), "r"(a), "r"(b), "r"(c), "r"(d) : "memory");
}
__device__ __forceinline__ uint32_t lds32(uint32_t a) { uint32_t v; asm volatile("ld.volatile.shared.u32 %0, [%1];" : "=r"(v) : "r"(a) : "memory"); return v; }
__device__ __forceinline__ void lds128(uint32_t (&v)[4], uint32_t a) {
    asm volatile("ld.shared.v4.u32 {%0,%1,%2,%3}, [%4];" : "=r"(v[0]), "=r"(v[1]), "=r"(v[2]), "=r"(v[3]) : "r"(a) : "memory");
}
__device__ __forceinline__ void lds128f(float& a, float& b, float& c, float& d, uint32_t p) {
    asm volatile("ld.shared.v4.f32 {%0,%1,%2,%3}, [%4];" : "=f"(a), "=f"(b), "=f"(c), "=f"(d) : "r"(p) : "memory");
}
__device__ __forceinline__ void lds64f(float& a, float& b, uint32_t p) {
    asm volatile("ld.shared.v2.f32 {%0,%1}, [%2];" : "=f"(a), "=f"(b) : "r"(p) : "memory");
}
__device__ __forceinline__ uint2 lds64(uint32_t a) { uint2 v; asm volatile("ld.volatile.shared.v2.u32 {%0,%1}, [%2];" : "=r"(v.x), "=r"(v.y) : "r"(a) : "memory"); return v; }
__device__ __forceinline__ void sts64(uint32_t p, uint32_t a, uint32_t b) { asm volatile("st.shared.v2.u32 [%0], {%1,%2};" :: "r"(p), "r"(a), "r"(b) : "memory"); }
__device__ __forceinline__ void sts128(uint32_t p, uint32_t a, uint32_t b, uint32_t c, uint32_t d) {
    asm volatile("st.shared.v4.u32 [%0], {%1,%2,%3,%4};" :: "r"(p), "r"(a), "r"(b), "r"(c), "r"(d) : "memory");
}
__device__ __forceinline__ void sts128f(uint32_t p, float a, float b, float c, float d) {
    asm volatile("st.shared.v4.f32 [%0], {%1,%2,%3,%4};" :: "r"(p), "f"(a), "f"(b), "f"(c), "f"(d) : "memory");
}
__device__ __forceinline__ void sts64f(uint32_t p, float a, float b) {
    asm volatile("st.shared.v2.f32 [%0], {%1,%2};" :: "r"(p), "f"(a), "f"(b) : "memory");
}
__device__ __forceinline__ float ex2(float x) { float r; asm("ex2.approx.ftz.f32 %0, %1;" : "=f"(r) : "f"(x)); return r; }
__device__ __forceinline__ float rcp(float x) { float r; asm("rcp.approx.ftz.f32 %0, %1;" : "=f"(r) : "f"(x)); return r; }
template <class T> __device__ __forceinline__ void pin64(T*& p) { asm volatile("" : "+l"(p)); }
__device__ __forceinline__ void pin32(uint32_t& v) { v = __shfl_sync(~0u, v, threadIdx.x & 31); }
template <class T> __device__ __forceinline__ T* pxor(T* p, uint32_t m) { return (T*)((uintptr_t)p ^ (uintptr_t)m); }

#define POLL_FAIL() (--budget < 0)
#define SCHED_FENCE() do { if (budget == -0x40000000) asm volatile("trap;"); } while (0)
__device__ __forceinline__ void wait_until(uint32_t t0, int d) { while ((int)(clk32() - t0) < d) {} }
#define PT(idx) do {} while (0)

__device__ __noinline__ void spare_cta(const __nv_bfloat16* __restrict__ x, const __nv_bfloat16* __restrict__ gate_w, int idx) {
    const int lane = threadIdx.x & 31, warp = threadIdx.x >> 5;
    uint4 gv[4];
    #pragma unroll
    for (int u = 0; u < 4; u++) gv[u] = __ldg((const uint4*)gate_w + u * 32 + lane);
    #pragma unroll 1
    for (int r0 = (idx * 8 + warp) * 8; r0 < S_; r0 += 256) {
        uint4 xv[8][4];
        #pragma unroll
        for (int j = 0; j < 8; j++)
            #pragma unroll
            for (int u = 0; u < 4; u++) xv[j][u] = __ldg((const uint4*)(x + (size_t)(r0 + j) * D_) + u * 32 + lane);
        #pragma unroll
        for (int j = 0; j < 8; j++) {
            float a = 0.f;
            #pragma unroll
            for (int u = 0; u < 4; u++)
                a += bf_lo(xv[j][u].x) * bf_lo(gv[u].x) + bf_hi(xv[j][u].x) * bf_hi(gv[u].x) + bf_lo(xv[j][u].y) * bf_lo(gv[u].y) + bf_hi(xv[j][u].y) * bf_hi(gv[u].y)
                   + bf_lo(xv[j][u].z) * bf_lo(gv[u].z) + bf_hi(xv[j][u].z) * bf_hi(gv[u].z) + bf_lo(xv[j][u].w) * bf_lo(gv[u].w) + bf_hi(xv[j][u].w) * bf_hi(gv[u].w);
            #pragma unroll
            for (int o = 16; o > 0; o >>= 1) a += __shfl_xor_sync(~0u, a, o);
            if (lane == 0) g_gate[r0 + j] = 1.f / (1.f + __expf(-a));
        }
    }
    __threadfence();
    __syncthreads();
    __threadfence();
    asm volatile("griddepcontrol.launch_dependents;" ::: "memory");
}

__global__ void __launch_bounds__(256, 1)
recur_kernel(const __grid_constant__ CUtensorMap tm_wq, const __grid_constant__ CUtensorMap tm_wk,
             const __grid_constant__ CUtensorMap tm_wv, const __grid_constant__ CUtensorMap tm_wo,
             const __grid_constant__ CUtensorMap tm_x, const __grid_constant__ CUtensorMap tm_kv,
             const __grid_constant__ CUtensorMap tm_q, const __nv_bfloat16* __restrict__ mem0,
             const __nv_bfloat16* __restrict__ x, const __nv_bfloat16* __restrict__ gate_w) {
    extern __shared__ unsigned char smem_raw[];
    constexpr uint32_t sb = 1024;
    if (smem_u32(smem_raw) != sb) { g_err = 9; asm volatile("trap;"); }
    const int tid = threadIdx.x, lane = tid & 31;
    const int warp = __shfl_sync(~0u, tid >> 5, 0);
    const int wg = warp >> 2, w4 = warp & 3;
    const uint32_t bar_w = sb + R_BAR;
    unsigned char* const comm = comm_base();
    TL(1, 0);
    const uint32_t t_start = clk32();
    {
        const uint4 z = make_uint4(0, 0, 0, 0);
        #pragma unroll
        for (int e = 0; e < 4; e++) ((uint4*)(comm + OFF_P1 + blockIdx.x * 16384))[e * 256 + tid] = z;
        if (tid < 2) *(uint4*)(comm + OFF_PROBE + tid * 4096 + blockIdx.x * 16) = z;
    }
    __syncthreads();
    if (warp < 4 && lane == 0) {
        unsigned char* const pb = comm + (warp >= 2 ? OFF_P1 + blockIdx.x * 16384 : OFF_PROBE + blockIdx.x * 16) + (warp & 1) * 4096;
        uint32_t best = 0xffffffffu;
        #pragma unroll 1
        for (int r = 0; r < NPROBE; r++) {
            const uint32_t t0 = clk32();
            uint32_t v, t1;
            asm volatile("atom.relaxed.gpu.global.add.u32 %0, [%1], 0;" : "=r"(v) : "l"(pb) : "memory");
            asm volatile("{ .reg .pred p; setp.ne.u32 p, %1, 0x7fc17fc3; mov.u32 %0, 0; @p mov.u32 %0, %%clock; }" : "=r"(t1) : "r"(v) : "memory");
            best = min(best, t1 - t0);
        }
        asm volatile("st.shared.u32 [%0], %1;" :: "r"(sb + R_SEL + 16 + warp * 4), "r"(best) : "memory");
    }
    bool first = false;
    uint32_t smid;
    asm volatile("mov.u32 %0, %%smid;" : "=r"(smid));
    unsigned int* const tab = (unsigned int*)(comm + OFF_SELT + 512);
    if (tid == 128) first = atomicCAS(tab + 4 + (smid >> 1), 0u, 1u) == 0u;
    __syncthreads();
    if (tid == 128) {
        const uint32_t side = lds32(sb + R_SEL + 20) < lds32(sb + R_SEL + 16) ? 1u : 0u;
        uint32_t role;
        int guard = 1 << 22;
        if (first) {
            const uint32_t t = atomicAdd(tab + side, 1u);
            uint32_t pair = side * 32 + t;
            if (t >= 32) {
                uint2 n;
                do { n = ldg64(tab); } while (n.x + n.y < gridDim.x / 2 && --guard > 0);
                const uint32_t other = side ? n.x : n.y;
                pair = other + (t - 32) < 32 ? (side ^ 1u) * 32 + other + (t - 32) : 64u + atomicAdd(tab + 2, 1u);
            }
            stg_rlx1(tab + 4 + (smid >> 1), pair + 2);
            role = pair * 2;
        } else {
            uint32_t v;
            do { asm volatile("ld.relaxed.gpu.global.u32 %0, [%1];" : "=r"(v) : "l"(tab + 4 + (smid >> 1)) : "memory"); } while (v < 2 && --guard > 0);
            role = (v - 2) * 2 + 1;
        }
        if (guard <= 0) { g_err = 5; role = 128; }
        sts128(sb + R_SEL, 0u, lds32(sb + R_SEL + 28) < lds32(sb + R_SEL + 24) ? 1u : 0u, side ^ MEMFLIP, ROLES ? role : blockIdx.x);
        wait_until(t_start, T_HOLD);
    }
    __syncthreads();
    const int bid = __shfl_sync(~0u, (int)lds32(sb + R_SEL + 12), 0);
    TL(1, 10);
    if (bid >= 128) { spare_cta(x, gate_w, bid - 128); return; }
    const int h = bid >> 2, ci = bid & 3, th = ci >> 1, kh = ci & 1;

    if (tid == 0) {
        for (int b = 0; b < 11; b++) mbar_init(bar_w + b * 8, 1);
        asm volatile("fence.mbarrier_init.release.cluster;" ::: "memory");
        const int col = h * 128 + th * 64, row = kh * 512;
        mbar_expect_tx(bar_w + 7 * 8, 32768);
        tma_3d(sb + R_XB, &tm_x, 0, 0, kh * 8, bar_w + 7 * 8);
        #pragma unroll
        for (int c = 0; c < 2; c++) {
            mbar_expect_tx(bar_w + (4 + c) * 8, 32768); tma_2d(sb + R_SP + c * 32768, &tm_wv, col, row + c * 256, bar_w + (4 + c) * 8);
        }
        #pragma unroll
        for (int c = 0; c < 2; c++) {
            mbar_expect_tx(bar_w + (0 + c) * 8, 32768); tma_2d(sb + (c ? R_SP + 65536 : R_XB + 32768), &tm_wq, col, row + c * 256, bar_w + (0 + c) * 8);
            mbar_expect_tx(bar_w + (2 + c) * 8, 32768); tma_2d(sb + R_WO + c * 32768, &tm_wk, col, row + c * 256, bar_w + (2 + c) * 8);
        }
        sts128(sb + R_SEL + 64, 0u, sb, sb, sb);
    }
    uint4 mv0, mv1;
    {
        const unsigned short* src = (const unsigned short*)mem0 + (kh * 2 + wg) * 256 + w4 * 32 + (lane & 19) + ((lane & 4) << 1) + ((lane & 8) >> 1);
        uint32_t w[8];
        #pragma unroll
        for (int e = 0; e < 8; e++) w[e] = (uint32_t)__ldg(src + (e >> 2) * 128 + (2 * (e & 3)) * D_) | ((uint32_t)__ldg(src + (e >> 2) * 128 + (2 * (e & 3) + 1) * D_) << 16);
        mv0 = make_uint4(w[0], w[1], w[2], w[3]); mv1 = make_uint4(w[4], w[5], w[6], w[7]);
    }
    {
        const uint4 z = make_uint4(0, 0, 0, 0);
        #pragma unroll
        for (int e = 0; e < 2; e++) ((uint4*)(comm + h * 32768 + ci * 8192))[e * 256 + tid] = z;
        if (tid < 32) *(uint4*)(comm + OFF_MEM + (tid >> 4) * 32768 + ci * 8192 + ((tid >> 3) & 1) * 4096 + h * 128 + (tid & 7) * 16) = z;
        if (tid < 3) ((uint4*)(comm + OFF_HCNT))[bid * 3 + tid] = z;
    }
    __syncthreads();
    TL(1, 1);
    const uint32_t lda = ((lane & 7) + ((lane >> 4) & 1) * 8) * 128 + (uint32_t)(((w4 * 2 + ((lane >> 3) & 1)) ^ (lane & 7)) * 16);
    uint32_t wA[32][4], wV[16][4];
    {
        mbar_wait(bar_w + (4 + wg) * 8, 0);
        #pragma unroll
        for (int k = 0; k < 16; k++) ldsm4t(wV[k], sb + R_SP + wg * 32768 + lda + k * 2048);
        mbar_wait(bar_w + (wg * 2 + wg) * 8, 0);
        #pragma unroll
        for (int k = 0; k < 16; k++) ldsm4t(wA[k], sb + (wg ? R_WO + 32768 : R_XB + 32768) + lda + k * 2048);
        mbar_wait(bar_w + (wg * 2 + (wg ^ 1)) * 8, 0);
        #pragma unroll
        for (int k = 0; k < 16; k++) ldsm4t(wA[16 + k], sb + (wg ? R_WO : R_SP + 65536) + lda + k * 2048);
    }
    __syncthreads();
    TL(1, 2);
    if (tid == 0) {
        mbar_expect_tx(bar_w + 8 * 8, 32768);
        tma_3d(sb + R_XB + 32768, &tm_x, 0, 32, kh * 8, bar_w + 8 * 8);
        mbar_expect_tx(bar_w + 6 * 8, 65536);
        #pragma unroll
        for (int t = 0; t < 4; t++) tma_2d(sb + R_WO + t * 16384, &tm_wo, ci * 256 + t * 64, h * 128, bar_w + 6 * 8);
    }
    int budget = POLL_LIMIT;
    uint32_t l8 = lane * 8;
#define LTAB(i) lds64(l8 + (sb + R_LT + (i) * 2048 + warp * 256))
    pin32(l8);
#define AFOFF(i) (K_WK ? ((i) & 1) * 32768 + ((i) >> 1) * 2048 : ((i) >> 3) * 32768 + ((i) & 7) * 2048)
#define L16 (l8 * 2)
#define LG (l8 >> 5)
    const float sc2 = 0.08838834764831845f * 1.4426950408889634f;

    float acc[16];
    auto x_issue_v1 = [&](uint64_t d) {
        WG_FENCE();
        #pragma unroll
        for (int k = 0; k < XV1; k++) wgmma_n32_rs(acc, wV[k], d + (k >> 2) * 256 + (k & 3) * 2, k != 0);
        WG_COMMIT();
    };
    auto x_issue_v2 = [&](uint64_t d) {
        if (XV1 < 16) {
            WG_FENCE();
            #pragma unroll
            for (int k = XV1; k < 16; k++) wgmma_n32_rs(acc, wV[k], d + (k >> 2) * 256 + (k & 3) * 2, 1);
            WG_COMMIT();
        }
    };
    auto x_issue_a = [&](auto lo, auto hi, uint64_t d) {
        constexpr int LO = decltype(lo)::value, HI = decltype(hi)::value;
        if (LO < HI) {
            WG_FENCE();
            #pragma unroll
            for (int k = LO; k < HI; k++) wgmma_n32_rs(acc, wA[k], (k < 16 ? d : d ^ 1024) + ((k & 15) >> 2) * 256 + (k & 3) * 2, k != 0);
            WG_COMMIT();
        }
    };
#define SBV() __shfl_sync(~0u, lds32(sb + R_SEL + 68), 0)
#define SBV3() do { sb0 = SBV(); sb1 = __shfl_sync(~0u, lds32(sb + R_SEL + 72), 0); sb2 = __shfl_sync(~0u, lds32(sb + R_SEL + 76), 0); } while (0)
#define XDESC(sbv, bb, half) mkdesc((sbv) + R_XB + (bb) * 32768 + (half) * 16384, 16, 1024, 1)
    auto v_dump = [&]() {
        const uint32_t vr = L16 + (sb + R_VRED + warp * 512);
        sts128(vr, pack_bf16(acc[0], acc[1]), pack_bf16(acc[4], acc[5]), pack_bf16(acc[2], acc[3]), pack_bf16(acc[6], acc[7]));
        sts128(vr + 4096, pack_bf16(acc[8], acc[9]), pack_bf16(acc[12], acc[13]), pack_bf16(acc[10], acc[11]), pack_bf16(acc[14], acc[15]));
    };
    auto v_final = [&](int ow) {
        uint32_t a[4], c[4];
        const uint32_t p = L16 + (sb + R_VRED + (ow >> 2) * 4096 + (ow & 3) * 512);
        lds128(a, p); lds128(c, p + 2048);
        sts128(L16 + (sb + R_AP + 8192 + (ow & 3) * 1024 + (ow >> 2) * 512), hadd2_bf16(a[0], c[0]), hadd2_bf16(a[1], c[1]),
               hadd2_bf16(a[2], c[2]), hadd2_bf16(a[3], c[3]));
    };
    auto a_park = [&]() {
        uint32_t w[8];
        #pragma unroll
        for (int j = 0; j < 8; j++) w[j] = movm(pack_bf16(acc[2 * j], acc[2 * j + 1]));
        if (wg) {
            sts128(L16 + (sb + R_AP + 4096 + w4 * 1024), w[0], w[1], w[2], w[3]);
            sts128(L16 + (sb + R_AP + 4096 + w4 * 1024 + 512), w[4], w[5], w[6], w[7]);
        } else {
            #pragma unroll
            for (int j = 0; j < 4; j++) sts64(l8 + (sb + R_AP + j * 1024 + w4 * 256), w[2 * j], w[2 * j + 1]);
        }
    };
    auto xp_out = [&](int seg) {
        unsigned char* d = comm + (OFF_XP + ((h * 4 + (seg & 3)) * 2 + th) * 12288);
        asm volatile("{ .reg .pred p; setp.ne.u32 p, %2, 0;\n"
                     "@p cp.reduce.async.bulk.global.shared::cta.bulk_group.add.noftz.bf16 [%0], [%1], %3;\n"
                     "@!p cp.async.bulk.global.shared::cta.bulk_group [%0], [%1], %3;\n"
                     "cp.async.bulk.commit_group; }" :: "l"(d), "r"(sb + R_AP), "r"(NOADD ? 0 : kh), "n"(XPB) : "memory");
    };
    auto xp_publish = [&](int seg) { bulk_wait_all(); stg_rlx1(comm + (OFF_FLAG + bid * 128), seg + 1); };
    auto xp_await = [&](int cta, int seg) {
        while (!__all_sync(~0u, (int)ldg_acq1(comm + (OFF_FLAG + cta * 128)) > seg) && !POLL_FAIL()) {}
        asm volatile("fence.proxy.async.global;" ::: "memory");
    };
    auto xs_issue = [&](int seg) {
        const uint32_t bar = bar_w + (9 + (seg & 1)) * 8, dst = sb + R_XS + (seg & 1) * 18432;
        mbar_expect_tx(bar, 18432);
        tma_3d(dst, &tm_kv, 0, 4, (h * 4 + (seg & 3)) * 2, bar);
        tma_3d(dst + 16384, &tm_q, 0, ci, (h * 4 + (seg & 3)) * 2, bar);
    };

    const int la = 4 - kh;
    TL(1, 3);
    #pragma unroll 1
    for (int seg = 0; seg < la; seg++) {
        mbar_wait(bar_w + (7 + (seg & 1)) * 8, (seg >> 1) & 1);
        TL(1, 4 + seg);
        { const uint64_t d = XDESC(SBV(), seg & 1, wg); x_issue_v1(d); x_issue_v2(d); } WG_WAIT(0);
        v_dump();
        x_issue_a(IC<0>(), IC<32>(), XDESC(SBV(), seg & 1, wg));
        if (warp == 5 && seg > 0) { if (elect_one()) xp_publish(seg - 1); }
        if (seg == 1 && tid == 32) {
            __threadfence();
            stg_rlx1(comm + OFF_SELT + bid * 4, 1u | (blockIdx.x * 16384 + lds32(sb + R_SEL + 4) * 4096));
            asm volatile("griddepcontrol.launch_dependents;" ::: "memory");
        }
        __syncthreads();
        v_final(warp);
        WG_WAIT(0);
        a_park();
        fence_async_smem();
        __syncthreads();
        if (seg + 1 < la) {
            if (warp == 5) {
                if (kh) xp_await(bid - 1, seg);
                if (elect_one()) xp_out(seg);
            }
            if (warp == 7) {
                if (elect_one()) {
                    mbar_expect_tx(bar_w + (7 + (seg & 1)) * 8, 32768);
                    tma_3d(sb + R_XB + (seg & 1) * 32768, &tm_x, 0, (2 + seg) * 32, kh * 8, bar_w + (7 + (seg & 1)) * 8);
                }
            }
        }
    }
    TL(1, 8);
    if (warp == 7) {
        xp_await(h * 4 + 1 + (lane & 1) * 2, 0);
        if (elect_one()) xs_issue(0);
    }
    const uint32_t sel_p1 = __shfl_sync(~0u, lds32(sb + R_SEL + 4), 0), sel_mem = __shfl_sync(~0u, lds32(sb + R_SEL + 8), 0);
    uint32_t inb0, inb1;
    {
        const int c = lane < 4 ? h * 4 + lane : (((lane >> 1) & 1) * 16 + warp * 2 + (lane & 1)) * 4 + ci;
        uint32_t v;
        do { v = ldg_acq1(comm + OFF_SELT + (c & 127) * 4); }
        while (!__all_sync(~0u, (v & 1u) != 0) && --budget >= 0);
        inb0 = __shfl_sync(~0u, v, 4 + (lane >> 4)) & ~1u; inb1 = __shfl_sync(~0u, v, 6 + (lane >> 4)) & ~1u;
    }
    {
        const int pw = th * 4 + w4;
        const int msl = kh * 2 + wg;
        uint32_t t = 0;
        if (lane == 0) t = h * 32768 + (pw >> 1) * 4096 + wg * 1024 + (pw & 1) * 512 + kh * 256;
        if (lane == 1) t = h * 32768 + (pw >> 1) * 4096 + 2048 + (pw & 1) * 1024 + kh * 512 + wg * 256;
        if (lane == 2) t = h * 32768 + (warp >> 1) * 4096;
        if (lane == 6) t = OFF_P1 + blockIdx.x * 16384 + sel_p1 * 4096 + (warp & 1) * 2048;
        if (lane == 7) t = OFF_MEM + ci * 8192 + h * 128 + (warp & 1) * 32;
        if (lane == 8) t = OFF_MEM + (2 * msl + (sel_mem ^ (msl & 1))) * 4096 + w4 * 512;
        if (lane == 9) t = sb + R_MEMT + wg * 4096;
        if (lane == 10) t = sb + R_MEMT + (wg ^ 1) * 4096;
        if (lane == 11) t = sb + R_SRED + (warp >> 1) * 2816 + (warp & 1) * 64;
        if (lane == 12) t = sb + R_SRED + warp * 352;
        if (lane == 13) t = sb + R_P + warp * 112;
        if (lane == 14) t = sb + R_OT + (warp >> 1) * 512 + (warp & 1) * 8;
        if (lane == 15) t = sb + R_XS + (warp >> 2) * 8192 + ((warp >> 1) & 1) * 2048 + (warp & 1) * 512;
        if (lane < 16) asm volatile("st.shared.u32 [%0], %1;" :: "r"(sb + R_TAB + warp * 64 + lane * 4), "r"(t) : "memory");
        __syncwarp();
    }
#define UTAB(i) __shfl_sync(~0u, lds32(sb + R_TAB + warp * 64 + (i) * 4), 0)
#define u_sex UTAB(2)
#define u_sp1 UTAB(6)
#define u_dmem UTAB(7)
#define u_smem UTAB(8)
    const uint32_t u_m0 = sb + R_MEMT + wg * 4096, u_m1 = sb + R_MEMT + (wg ^ 1) * 4096, u_sr = sb + R_SRED + warp * 352,
                   u_pw = sb + R_P + warp * 112, u_ow = sb + R_OT + (warp >> 1) * 512 + (warp & 1) * 8;
    {
        const uint32_t ld = OFF_P1 + h * 64 + ((lane >> 3) & 1) * 2048 + (lane & 7) * 8;
        sts64(sb + R_LT + tid * 8, ld + inb0, ld + inb1);
        sts64(sb + R_LT + 2048 + tid * 8, lda + sb + R_WO + wg * 16384, UTAB(15) + lane * 16);
        sts64(sb + R_LT + 4096 + tid * 8, UTAB(0) + lane * 8, UTAB(1) + lane * 8);
        sts64(sb + R_LT + 6144 + tid * 8, UTAB(11) + (lane >> 2) * 352 + (lane & 3) * 8,
              sb + R_MEMT + wg * 4096 + w4 * 512 + ((lane & 19) + ((lane & 4) << 1) + ((lane & 8) >> 1)) * 16);
        sts64(sb + R_LT + 8192 + tid * 8, UTAB(2) + lane * 8, OFF_FLAG + (warp == 5 ? (bid & ~1) : h * 4 + 1 + (lane & 1) * 2) * 128);
    }
    mbar_wait(bar_w + 9 * 8, 0);
    mbar_wait(bar_w + 6 * 8, 0);
    mbar_wait(bar_w + (7 + (la & 1)) * 8, (la >> 1) & 1);
    TL(1, 9);
    uint32_t sb0, sb1, sb2;
    SBV3();
    uint32_t a_st = LTAB(3).y;
    sts128(a_st, mv0.x, mv0.y, mv0.z, mv0.w); sts128(a_st + 2048, mv1.x, mv1.y, mv1.z, mv1.w);
    for (int s = 0;; s++) {
        const uint32_t tag = ((s >> 1) & 1) ^ 1;
        const uint32_t tm = tag - 1u;
        const uint32_t radd = tm & 0x10000u;
        const int bb = s & 1, seg = s + la, xb = seg & 1;
        asm volatile("" : "+r"(l8));
        const uint2 o_qv = LTAB(2);
        __syncthreads();
        auto x_fetch = [&]() {
            if (seg + 1 < NSEG) {
                if (elect_one()) {
                    mbar_expect_tx(bar_w + (7 + (xb ^ 1)) * 8, 32768);
                    tma_3d(sb + R_XB + (xb ^ 1) * 32768, &tm_x, 0, (seg + 1) * 32, kh * 8, bar_w + (7 + (xb ^ 1)) * 8);
                }
            }
        };
        if (!K_G2 && XTMA == 0 && RARE(warp == 7)) x_fetch();
        PT(1);
        {
            float a0[4] = {0.f, 0.f, 0.f, 0.f}, a1[4] = {0.f, 0.f, 0.f, 0.f}, a2[4] = {0.f, 0.f, 0.f, 0.f}, a3[4] = {0.f, 0.f, 0.f, 0.f};
            float v0[4] = {0.f, 0.f, 0.f, 0.f}, v1[4] = {0.f, 0.f, 0.f, 0.f};
            uint32_t b0[8][4];
            #pragma unroll
            for (int u = 0; u < 8; u++) {
                uint32_t b1[4];
                ldsm4t(b0[u], L16 + (u_m0 + u * 512));
                if (K_G2 == 1 && u == 0) { if (XTMA == 0 && RARE(warp == 7)) x_fetch(); }
                ldsm4t(b1, L16 + (u_m1 + u * 512));
                const int k = 2 * u;
                mma16816(a0, wA[k][0], wA[k][1], wA[k][2], wA[k][3], b0[u][0], b0[u][1]);
                if (u < 8 - K_VD) mma16816(v0, wV[k][0], wV[k][1], wV[k][2], wV[k][3], b0[u][0], b0[u][1]);
                mma16816(a1, wA[k + 1][0], wA[k + 1][1], wA[k + 1][2], wA[k + 1][3], b0[u][2], b0[u][3]);
                if (u < 8 - K_VD) mma16816(v1, wV[k + 1][0], wV[k + 1][1], wV[k + 1][2], wV[k + 1][3], b0[u][2], b0[u][3]);
                mma16816(a2, wA[16 + k][0], wA[16 + k][1], wA[16 + k][2], wA[16 + k][3], b1[0], b1[1]);
                mma16816(a3, wA[17 + k][0], wA[17 + k][1], wA[17 + k][2], wA[17 + k][3], b1[2], b1[3]);
            }
            if (K_VD) SCHED_FENCE();
            #pragma unroll
            for (int u = 8 - K_VD; u < 8; u++) {
                mma16816(v0, wV[2 * u][0], wV[2 * u][1], wV[2 * u][2], wV[2 * u][3], b0[u][0], b0[u][1]);
                mma16816(v1, wV[2 * u + 1][0], wV[2 * u + 1][1], wV[2 * u + 1][2], wV[2 * u + 1][3], b0[u][2], b0[u][3]);
            }
            float e0 = (a0[0] + a1[0]) + (a2[0] + a3[0]), e1 = (a0[1] + a1[1]) + (a2[1] + a3[1]);
            if ((l8 & 32) == 0) { e0 = pretag(e0, radd); e1 = pretag(e1, radd); }
            const uint32_t w0 = settag(movm(pack_bf16(e0, e1)), tag);
            const uint32_t w1 = movm(pack_bf16((a0[2] + a1[2]) + (a2[2] + a3[2]), (a0[3] + a1[3]) + (a2[3] + a3[3])));
            stg64((comm + bb * 16384) + o_qv.x, w0, w1);
            if (K_VD) SCHED_FENCE();
            stg64((comm + bb * 16384) + o_qv.y, settag(pack_bf16(pretag(v0[0] + v1[0], radd), v0[1] + v1[1]), tag), pack_bf16(v0[2] + v1[2], v0[3] + v1[3]));
        }
        SCHED_FENCE();
        uint32_t t_send = clk32();
        PT(2);
        uint2 va[4];
        uint32_t aw2;
        uint32_t flagv;
        uint32_t af[NAF][4];
        {
            const uint2 osx = LTAB(4);
            uint32_t kx0[4], kx1[4];
            uint2 q0, q1;
            auto kq_load = [&]() {
                const uint32_t aq = l8 + (sb + R_XS + 16384 + bb * 18432 + (warp >> 1) * 512);
                const uint32_t ak = L16 + (sb + R_XS + bb * 18432 + (warp >> 2) * 8192 + ((warp >> 1) & 1) * 2048 + (warp & 1) * 512);
                q0 = lds64(aq); q1 = lds64(aq + 256);
                lds128(kx0, ak); lds128(kx1, ak + 1024);
            };
            if (K_KXE) kq_load();
            const uint64_t dv = XDESC(sb0, xb, wg);
            if (!(SKIPW & 1)) x_issue_v1(dv);
            const unsigned char* sx = (comm + bb * 16384) + osx.x;
            const unsigned char* sf = comm + osx.y;
            fence_async_smem();
            wait_until(t_send, D_EX);
            const bool ev = (warp & 1) == 0;
            uint2 a[8];
            uint32_t flag = 0;
            auto ex_load = [&](uint2 (&r)[8], bool first) {
                #pragma unroll
                for (int u = 0; u < 4; u++) r[u] = ldg64(sx + u * 256);
                if (K_SYM || !first) {
                    #pragma unroll
                    for (int u = 4; u < 8; u++) r[u] = ldg64(sx + u * 256);
                    if (first) asm volatile("ld.relaxed.gpu.global.u32 %0, [%1];" : "=r"(flag) : "l"(sf) : "memory");
                } else {
                    #pragma unroll
                    for (int u = 4; u < 8; u++) { r[u].x = ~tm; r[u].y = 0u; }
                    if (ev) {
                        #pragma unroll
                        for (int u = 4; u < 8; u++) r[u] = ldg64(sx + u * 256);
                    } else {
                        asm volatile("ld.relaxed.gpu.global.u32 %0, [%1];" : "=r"(r[7].y) : "l"(sf) : "memory");
                    }
                }
            };
            ex_load(a, true);
            if (XV1 < 16) { SCHED_FENCE(); x_issue_v2(dv); }
            const uint2 awk = LTAB(1);
            if (!K_KXE) kq_load();
            SCHED_FENCE();
            WG_WAIT(0);
            if (!(SKIPW & 1)) v_dump();
            const uint32_t sr = LTAB(3).x;
            #pragma unroll
            for (int k = 0; k < NAF1; k++) ldsm4t(af[k], awk.x + AFOFF(k));
            SCHED_FENCE();
            PT(3);
            uint32_t qk[8];
            auto ex_ok = [&](const uint2 (&r)[8]) {
                return __all_sync(~0u, and3(and3(chk2(r[0].x, r[1].x, tm), chk2(r[2].x, r[3].x, tm), chk2(r[4].x, r[5].x, tm)), chk2(r[6].x, r[7].x, tm), 1u) != 0);
            };
            auto ex_sum = [&](const uint2 (&r)[8]) {
                #pragma unroll
                for (int u = 0; u < 4; u++) { qk[2 * u] = hadd2_bf16(r[2 * u].x, r[2 * u + 1].x); qk[2 * u + 1] = hadd2_bf16(r[2 * u].y, r[2 * u + 1].y); }
            };
            float sa[3][4];
            auto scores = [&]() {
                #pragma unroll
                for (int j = 0; j < 3; j++) { sa[j][0] = sa[j][1] = sa[j][2] = sa[j][3] = 0.f; }
                #pragma unroll
                for (int ks = 0; ks < 2; ks++) {
                    const uint32_t x0 = ks ? q1.x : q0.x, x1 = ks ? q1.y : q0.y;
                    mma16816(sa[0], qk[2 * ks], x0, qk[2 * ks + 1], x1, ks ? kx1[0] : kx0[0], ks ? kx1[1] : kx0[1]);
                    mma16816(sa[1], qk[2 * ks], x0, qk[2 * ks + 1], x1, ks ? kx1[2] : kx0[2], ks ? kx1[3] : kx0[3]);
                    mma16816(sa[2], qk[2 * ks], x0, qk[2 * ks + 1], x1, qk[4 + 2 * ks], qk[5 + 2 * ks]);
                }
            };
            flagv = K_SYM ? flag : a[7].y;
            if (K_SPEC) {
                ex_sum(a);
                scores();
                if (RARE(!ex_ok(a))) {
                    bool ok;
                    do { uint2 r[8]; ex_load(r, false); ex_sum(r); ok = ex_ok(r); } while (!ok && !POLL_FAIL());
                    kq_load();
                    scores();
                }
            } else {
                if (K_PHI) {
                    ex_sum(a);
                    if (RARE(!ex_ok(a))) {
                        bool ok;
                        do { uint2 r[8]; ex_load(r, false); ex_sum(r); ok = ex_ok(r); } while (!ok && !POLL_FAIL());
                    }
                } else {
                    while (RARE(!ex_ok(a)) && !POLL_FAIL()) ex_load(a, false);
                    ex_sum(a);
                }
                scores();
            }
            PT(4);
            sts64f(sr, sa[0][0], sa[0][1]); sts64f(sr + 32, sa[1][0], sa[1][1]);
            sts64f(sr + 160, sa[0][2], sa[0][3]); sts64f(sr + 192, sa[1][2], sa[1][3]);
            if (ev) { sts64f(sr + 128, sa[2][0], sa[2][1]); sts64f(sr + 288, sa[2][2], sa[2][3]); }
            const unsigned char* sv = sx + (2048 + (warp & 1) * 1024);
            #pragma unroll
            for (int u = 0; u < 4; u++) va[u] = ldg64(sv + u * 256);
            aw2 = NAF2 > NAF1 ? LTAB(1).x : 0u;
        }
        #pragma unroll
        for (int k = NAF1; k < NAF2; k++) ldsm4t(af[k], aw2 + AFOFF(k));
        auto xp_in = [&]() {
            if (s + 1 < NSEG) {
                if (!__all_sync(~0u, (int)flagv > s + 1)) xp_await(h * 4 + 1 + (l8 & 8) / 4, s + 1);
                asm volatile("fence.proxy.async.global;" ::: "memory");
                if (elect_one()) xs_issue(s + 1);
            }
        };
        auto xp_pre = [&]() {
            if (kh && seg - 1 < NSEG && !__all_sync(~0u, (int)flagv > seg - 1)) xp_await(bid - 1, seg - 1);
            asm volatile("fence.proxy.async.global;" ::: "memory");
        };
        if (XSPOS == 0) { if (RARE((warp | 2) == 7)) { if (warp == 7) xp_in(); else xp_pre(); } }
        else if (warp == 5) xp_pre();
        if (XTMA == 1 && warp == 1) x_fetch();
        const bool xr = l8 >= 80;
        int lim = (xr && l8 < 144) ? ci * 8 + warp + 40 - (int)(l8 >> 1) : 64;
        uint32_t a_sc = (K_SOFT ? min(l8, 152u) * 2 : L16) + u_sr;
        if (K_SOFT) asm volatile("" : "+r"(lim), "+r"(a_sc));
        __syncthreads();
        if (RARE(warp == 5 && seg - 1 < NSEG)) { if (elect_one()) xp_out(seg - 1); }
        PT(5);
        uint32_t vm0, vm1, vxa[4], vxb[4];
        auto v_check = [&](uint32_t tm2) {
            auto v_take = [&](const uint2 (&r)[4], uint32_t m) {
                vm0 = hadd2_bf16(hadd2_bf16(r[0].x, r[1].x), hadd2_bf16(r[2].x, r[3].x));
                vm1 = hadd2_bf16(hadd2_bf16(r[0].y, r[1].y), hadd2_bf16(r[2].y, r[3].y));
                return __all_sync(~0u, and3(chk2(r[0].x, r[1].x, m), chk2(r[2].x, r[3].x, m), 1u) != 0);
            };
            if (K_VCHK == 2) { va[0].x ^= tm2 ^ tm; va[0].y ^= tm2 ^ tm; }
            if (RARE(!v_take(va, tm2))) {
                const unsigned char* sv = (comm + (bb * 16384 + 2048 + (warp & 1) * 1024)) + LTAB(4).x;
                bool ok;
                do {
                    uint2 r[4];
                    #pragma unroll
                    for (int u = 0; u < 4; u++) r[u] = ldg64(sv + u * 256);
                    ok = v_take(r, tm);
                } while (!ok && !POLL_FAIL());
            }
        };
        auto vx_load = [&]() { const uint32_t av = L16 + (sb + R_XS + 4096 + bb * 18432 + wg * 8192 + w4 * 1024); lds128(vxa, av); lds128(vxb, av + 512); };
        {
            float v[4], t[4][4];
            #pragma unroll
            for (int w = 0; w < 4; w++) {
                if (K_SOFT) lds128f(t[w][0], t[w][1], t[w][2], t[w][3], a_sc + w * 2816);
                else {
                    t[w][0] = t[w][1] = t[w][2] = t[w][3] = 0.f;
                    asm volatile("{ .reg .pred p; setp.lt.u32 p, %5, 160; @p ld.shared.v4.f32 {%0,%1,%2,%3}, [%4]; }"
                                 : "+f"(t[w][0]), "+f"(t[w][1]), "+f"(t[w][2]), "+f"(t[w][3]) : "r"(a_sc + w * 2816), "r"(l8) : "memory");
                }
            }
            if (K_VCHK) vx_load();
            #pragma unroll
            for (int e = 0; e < 4; e++) v[e] = (t[0][e] + t[1][e]) + (t[2][e] + t[3][e]);
            #pragma unroll
            for (int e = 0; e < 4; e++) if (e > lim) v[e] = -1.0e9f / 0.08838834764831845f;
            const float mxl = fmaxf(fmaxf(v[0], v[1]), fmaxf(v[2], v[3]));
            int key = __float_as_int(mxl); key ^= (key >> 31) & 0x7fffffff;
            const int m0 = __reduce_max_sync(~0u, xr ? (int)0x80000000 : key);
            const int m1 = __reduce_max_sync(~0u, (xr && (K_SOFT || l8 < 160)) ? key : (int)0x80000000);
            int mk = xr ? m1 : m0; mk ^= (mk >> 31) & 0x7fffffff;
            const float mx = __int_as_float(mk);
            const uint32_t p0 = pack_bf16(ex2((v[0] - mx) * sc2), ex2((v[1] - mx) * sc2));
            const uint32_t p1 = pack_bf16(ex2((v[2] - mx) * sc2), ex2((v[3] - mx) * sc2));
            if (l8 < 160) sts64(l8 + (xr ? 8 * 112 - 80 : 0) + u_pw, p0, p1);
            if (!K_VCHK) {
                uint32_t tm2 = tm; asm volatile("{ .reg .pred p; setp.eq.u32 p, %1, 0x7fc17fc3; @p not.b32 %0, %0; }" : "+r"(tm2) : "r"(p1));
                v_check(tm2);
            }
        }
        if (XTMA == 2 && warp == 1) x_fetch();
        if (XSPOS == 3 && warp == 7) xp_in();
        const uint32_t a_wo = LTAB(1).x;
        if (!K_VCHK) vx_load();
        __syncthreads();
        PT(6);
        uint32_t ox0, ox1;
        float im;
        {
            uint32_t p0[4], p1[4], pm[2];
            const uint32_t pa = (l8 & 0x78) * 14 + (sb + R_P);
            const uint32_t zero = K_VCHK ? lds32(sb + R_SEL + 64) : 0u;
            ldsm4(p0, pa + ((l8 >> 3) & 16)); ldsm4(p1, pa + 32 + ((l8 >> 3) & 16)); ldsm2(pm, pa + 64);
            if (K_VCHK) v_check(tm ^ zero);
            float lo[4] = {0.f, 0.f, 0.f, 0.f}, hi[4] = {0.f, 0.f, 0.f, 0.f}, sm[4] = {0.f, 0.f, 0.f, 0.f};
            float lo2[4] = {0.f, 0.f, 0.f, 0.f}, hi2[4] = {0.f, 0.f, 0.f, 0.f};
            const uint32_t ones = 0x3f803f80u;
            if (!K_DN) mma16816(sm, p0[0], p0[1], p0[2], p0[3], ones, ones);
            mma16816(lo, p0[0], p0[1], p0[2], p0[3], vxa[0], vxa[1]);
            mma16816(hi, p0[0], p0[1], p0[2], p0[3], vxa[2], vxa[3]);
            if (!K_DN) mma16816(sm, p1[0], p1[1], p1[2], p1[3], ones, ones);
            mma16816(K_PV ? lo2 : lo, p1[0], p1[1], p1[2], p1[3], vxb[0], vxb[1]);
            mma16816(K_PV ? hi2 : hi, p1[0], p1[1], p1[2], p1[3], vxb[2], vxb[3]);
            if (!K_DN) mma1688(sm, pm[0], pm[1], ones);
            mma1688(lo, pm[0], pm[1], vm0);
            mma1688(hi, pm[0], pm[1], vm1);
            if (K_DN) {
                mma16816(sm, p0[0], p0[1], p0[2], p0[3], ones, ones);
                mma16816(sm, p1[0], p1[1], p1[2], p1[3], ones, ones);
                mma1688(sm, pm[0], pm[1], ones);
            }
            if (K_PV) {
                #pragma unroll
                for (int e = 0; e < 4; e++) { lo[e] += lo2[e]; hi[e] += hi2[e]; }
            }
            if (K_DN) sts64(L16 + u_ow, pack_bf16(lo[0], lo[1]), pack_bf16(hi[0], hi[1]));
            #pragma unroll
            for (int k = NAF2; k < NAF; k++) ldsm4t(af[k], a_wo + AFOFF(k));
            im = rcp(sm[0]);
            const float ix = rcp(sm[2]);
            if (!K_DN) sts64(L16 + u_ow, pack_bf16(lo[0] * im, lo[1] * im), pack_bf16(hi[0] * im, hi[1] * im));
            ox0 = pack_bf16(lo[2] * ix, lo[3] * ix); ox1 = pack_bf16(hi[2] * ix, hi[3] * ix);
        }
        if (!K_VF3 && !K_NB && warp == 5) bulk_wait_read();
        if (XTMA == 3 && warp == 1) x_fetch();
        const uint2 ldp = LTAB(0);
        __syncthreads();
        if (XSPOS == 1 && warp == 7) xp_in();
        PT(7);
        {
            uint32_t ob[4][4];
            #pragma unroll
            for (int w = 0; w < 4; w++) lds128(ob[w], L16 + (sb + R_OT + w * 512));
            float n0 = 1.f, n1 = 1.f;
            if (K_DN) { n0 = __shfl_sync(~0u, im, l8 & 24); n1 = __shfl_sync(~0u, im, (l8 & 24) + 4); }
            unsigned char* dd0 = comm + (ldp.x ^ (bb * 0x3000));
            unsigned char* dd1 = comm + (ldp.y ^ (bb * 0x3000));
            if (K_WK) {
                float c[2 * WCH][4];
                #pragma unroll
                for (int e = 0; e < 2 * WCH; e++) { c[e][0] = c[e][1] = c[e][2] = c[e][3] = 0.f; }
                #pragma unroll
                for (int i = 0; i < WOCUT; i++) {
                    const int k = i >> 1;
                    mma16816(c[i % (2 * WCH)], af[i % NAF][0], af[i % NAF][1], af[i % NAF][2], af[i % NAF][3], ob[k >> 1][(k & 1) * 2], ob[k >> 1][(k & 1) * 2 + 1]);
                    if (i + NAF < WOCUT) ldsm4t(af[i % NAF], a_wo + AFOFF(i + NAF));
                }
                #pragma unroll
                for (int t = 0; t < 2; t++) {
                    float f[4];
                    #pragma unroll
                    for (int e = 0; e < 4; e++) f[e] = (WCH > 1 ? c[t][e] + c[(t + 2) % (2 * WCH)][e] : c[t][e]) * ((e & 1) ? n1 : n0);
                    stg64(t ? dd1 : dd0, settag(pack_bf16(pretag(f[0], radd), f[1]), tag), pack_bf16(f[2], f[3]));
                }
            } else {
                #pragma unroll
                for (int t = 0; t < 2; t++) {
                    float c0[4] = {0.f, 0.f, 0.f, 0.f}, c1[4] = {0.f, 0.f, 0.f, 0.f};
                    #pragma unroll
                    for (int k = 0; k < 8; k++) {
                        const int i = t * 8 + k;
                        if (k & 1) mma16816(c1, af[i % NAF][0], af[i % NAF][1], af[i % NAF][2], af[i % NAF][3], ob[k >> 1][2], ob[k >> 1][3]);
                        else       mma16816(c0, af[i % NAF][0], af[i % NAF][1], af[i % NAF][2], af[i % NAF][3], ob[k >> 1][0], ob[k >> 1][1]);
                        if (i + NAF < 16) ldsm4t(af[i % NAF], a_wo + AFOFF(i + NAF));
                    }
                    const uint32_t w0 = settag(pack_bf16((c0[0] + c1[0]) * n0, (c0[1] + c1[1]) * n1), tag), w1 = pack_bf16((c0[2] + c1[2]) * n0, (c0[3] + c1[3]) * n1);
                    stg64(t ? dd1 : dd0, w0, w1);
                    if (WOFENCE && t == 0) SCHED_FENCE();
                }
            }
        }
        SCHED_FENCE();
        t_send = clk32();
        PT(8);
        auto ox_store = [&]() {
            const bool od = l8 & 8;
            const uint32_t t = __shfl_xor_sync(~0u, od ? ox0 : ox1, 1);
            *(uint2*)(g_ox + (size_t)(s * 32 + ci * 8 + LG) * HD_ + h * 128 + warp * 16 + (od ? 8 : 0) + ((l8 >> 2) & 4)) =
                od ? make_uint2(t, ox1) : make_uint2(ox0, t);
        };
        if (!K_OXL || s + 1 == NSEG) ox_store();
        if (s + 1 == NSEG) break;
        if (XTMA == 4 && warp == 1) x_fetch();
        if (XSPOS == 2 && warp == 7) xp_in();
        x_issue_a(IC<0>(), IC<NA0>(), XDESC(sb1, xb, wg));
        if (NA1 > NA0 && wg) x_issue_a(IC<NA0>(), IC<NA1>(), XDESC(sb1, xb, wg));
        if (K_OXL) { SCHED_FENCE(); ox_store(); }
        PT(9);
        if ((warp >> 1) == RW / 2 || (K_R2 && warp >= 6)) {
            const unsigned char* sp = (comm + (u_sp1 ^ (bb * 0x3000))) + ((l8 & 24) * 8 + (l8 >> 5) * 8);
            unsigned char* dm = (comm + (u_dmem + bb * 32768)) + ((l8 & 0x40) * 64 + (l8 & 0x20) * 2 + (l8 & 24));
            const uint32_t e0m = (l8 & 32) ? 0u : 0x00003f80u, e1m = e0m << 16, e2m = e0m ^ 0x00003f80u, e3m = e2m << 16;
            auto p_load = [&](uint2 (&a)[8]) {
                #pragma unroll
                for (int u = 0; u < 8; u++) a[u] = ldg64(sp + u * 256);
            };
            auto p_ok = [&](const uint2 (&a)[8]) {
                return __all_sync(~0u, and3(and3(chk2(a[0].x, a[1].x, tm), chk2(a[2].x, a[3].x, tm), chk2(a[4].x, a[5].x, tm)), chk2(a[6].x, a[7].x, tm), 1u) != 0);
            };
            auto p_red = [&](const uint2 (&a)[8]) {
                float r[2][4];
                #pragma unroll
                for (int e = 0; e < 2; e++) { r[e][0] = r[e][1] = r[e][2] = r[e][3] = 0.f; }
                float r2[2][4];
                #pragma unroll
                for (int e = 0; e < 2; e++) { r2[e][0] = r2[e][1] = r2[e][2] = r2[e][3] = 0.f; }
                #pragma unroll
                for (int u = 0; u < 8; u++) {
                    if (K_P2 || (u & 2) == 0) mma16816(r[u & 1], e0m, e1m, e2m, e3m, a[u].x, a[u].y);
                    else mma16816(r2[u & 1], e0m, e1m, e2m, e3m, a[u].x, a[u].y);
                }
                float f[4];
                #pragma unroll
                for (int e = 0; e < 4; e++) f[e] = K_P2 ? r[0][e] + r[1][e] : (r[0][e] + r[1][e]) + (r2[0][e] + r2[1][e]);
                if (l8 < 128) stg64(dm, settag(pack_bf16(pretag(f[0], radd), f[2]), tag), pack_bf16(f[1], f[3]));
                SCHED_FENCE();
                PT(13);
            };
            uint2 a[8];
            wait_until(t_send, D_P1 + (K_R2 ? wg * D_P2 : 0));
            if (K_P2) {
                uint2 c[8];
                p_load(a);
                wait_until(t_send, D_P1 + D_P2);
                while (true) {
                    p_load(c);
                    if (p_ok(a) || POLL_FAIL()) { p_red(a); break; }
                    p_load(a);
                    if (p_ok(c)) { p_red(c); break; }
                }
            } else {
                do { p_load(a); } while (!p_ok(a) && !POLL_FAIL());
                PT(10);
                p_red(a);
            }
        } else {
            if (K_R2) {
                v_final(warp); v_final(warp + 2);
                if (warp == 5) { if (seg - 1 < NSEG) { if (elect_one()) xp_publish(seg - 1); } }
                else if (warp == 1) mbar_wait(bar_w + (9 + (bb ^ 1)) * 8, ((s + 1) >> 1) & 1);
                else if (warp == 0) { if (XTMA < 3 && seg + 1 < NSEG) mbar_wait(bar_w + (7 + (xb ^ 1)) * 8, ((seg + 1) >> 1) & 1); }
            } else if (warp == 5) {
                if (seg - 1 < NSEG) { if (elect_one()) xp_publish(seg - 1); }
                if (K_NB && !K_VF3) { __syncwarp(); bar_arrive(1, 192); }
            } else {
                if (K_NB && !K_VF3) bar_sync(1, 192);
                if (!K_VF3) v_final(warp);
                if (warp < 5) { if (!K_VF3) v_final(warp == 4 ? 5 : RW + (warp & 1)); }
                else if (warp == 7) mbar_wait(bar_w + (9 + (bb ^ 1)) * 8, ((s + 1) >> 1) & 1);
                else { if (XTMA == 5) x_fetch(); if (XTMA < 3 && seg + 1 < NSEG) mbar_wait(bar_w + (7 + (xb ^ 1)) * 8, ((seg + 1) >> 1) & 1); }
            }
        }
        const uint32_t o_sm = u_smem;
        __syncthreads();
        t_send = clk32();
        PT(11);
        const uint64_t dh = XDESC(sb2, xb, wg);
        if (NA1 > NA0 && !wg) x_issue_a(IC<NA0>(), IC<NA1>(), dh);
        x_issue_a(IC<NA1>(), IC<32>(), dh);
        {
            const unsigned char* sm = (comm + (o_sm + bb * 32768)) + L16;
            wait_until(t_send, D_MEM);
            mv0 = ldg128(sm); mv1 = ldg128(sm + 2048);
            if (K_VF3) v_final(warp);
            SBV3();
            a_st = LTAB(3).y;
            if (K_MS) { wait_until(t_send, D_MEM + D_MS); cpa16(a_st, sm); cpa16(a_st + 2048, sm + 2048); cpa_commit(); }
            WG_WAIT(0);
            if (K_MS > 1) { cpa16(a_st, sm); cpa16(a_st + 2048, sm + 2048); cpa_commit(); }
            if (!(SKIPW & 6)) a_park();
            if (XTMA >= 3 && warp == 6 && seg + 1 < NSEG) mbar_wait(bar_w + (7 + (xb ^ 1)) * 8, ((seg + 1) >> 1) & 1);
            SCHED_FENCE();
            PT(12);
            if (K_MS) {
                if (__all_sync(~0u, and3(chk2(mv0.x, mv0.z, tm), chk2(mv1.x, mv1.z, tm), 1u) != 0)) {
                    sts128(a_st, mv0.x, mv0.y, mv0.z, mv0.w); sts128(a_st + 2048, mv1.x, mv1.y, mv1.z, mv1.w);
                } else {
                    while (true) {
                        cpa16(a_st, sm); cpa16(a_st + 2048, sm + 2048); cpa_commit();
                        CPA_WAIT(K_MS);
                        uint32_t m0[4], m1[4];
                        lds128(m0, a_st); lds128(m1, a_st + 2048);
                        if (__all_sync(~0u, and3(chk2(m0[0], m0[2], tm), chk2(m1[0], m1[2], tm), 1u) != 0) || POLL_FAIL()) break;
                    }
                }
            } else {
                while (true) {
                    if (__all_sync(~0u, and3(chk2(mv0.x, mv0.z, tm), chk2(mv1.x, mv1.z, tm), 1u) != 0) || POLL_FAIL()) break;
                    mv0 = ldg128(sm); mv1 = ldg128(sm + 2048);
                }
                sts128(a_st, mv0.x, mv0.y, mv0.z, mv0.w); sts128(a_st + 2048, mv1.x, mv1.y, mv1.z, mv1.w);
            }
        }
        PT(0);
    }
    TL(1, 13);
    if (warp == 5) bulk_wait_read();
    if (budget < 0) g_err = 2;
}

typedef CUresult (*EncodeFn)(CUtensorMap*, CUtensorMapDataType, cuuint32_t, void*, const cuuint64_t*, const cuuint64_t*,
                             const cuuint32_t*, const cuuint32_t*, CUtensorMapInterleave, CUtensorMapSwizzle,
                             CUtensorMapL2promotion, CUtensorMapFloatOOBfill);

void make_2d(EncodeFn enc, CUtensorMap* m, const void* p, uint64_t rows, uint64_t cols, uint32_t box_c, uint32_t box_r) {
    cuuint64_t dims[2] = {cols, rows}; cuuint64_t str[1] = {cols * 2};
    cuuint32_t box[2] = {box_c, box_r}, es[2] = {1, 1};
    enc(m, CU_TENSOR_MAP_DATA_TYPE_BFLOAT16, 2, (void*)p, dims, str, box, es, CU_TENSOR_MAP_INTERLEAVE_NONE,
        CU_TENSOR_MAP_SWIZZLE_128B, L2P, CU_TENSOR_MAP_FLOAT_OOB_FILL_NONE);
}
void make_3d(EncodeFn enc, CUtensorMap* m, const void* p, uint64_t rows, uint64_t cols, uint32_t inner, uint32_t box_r, uint32_t groups) {
    cuuint64_t dims[3] = {inner, rows, cols / inner}; cuuint64_t str[2] = {cols * 2, (cuuint64_t)inner * 2};
    cuuint32_t box[3] = {inner, box_r, groups}, es[3] = {1, 1, 1};
    enc(m, CU_TENSOR_MAP_DATA_TYPE_BFLOAT16, 3, (void*)p, dims, str, box, es, CU_TENSOR_MAP_INTERLEAVE_NONE,
        inner == 64 ? CU_TENSOR_MAP_SWIZZLE_128B : CU_TENSOR_MAP_SWIZZLE_64B, L2P,
        CU_TENSOR_MAP_FLOAT_OOB_FILL_NONE);
}

}

extern "C" void kernel_launch(void* const* d_in, const int* in_sizes, int n_in, void* d_out, int out_size) {
    (void)in_sizes; (void)n_in; (void)out_size;
    const __nv_bfloat16* x = (const __nv_bfloat16*)d_in[0];
    const __nv_bfloat16* mem0 = (const __nv_bfloat16*)d_in[1];
    const __nv_bfloat16* wq = (const __nv_bfloat16*)d_in[2];
    const __nv_bfloat16* wk = (const __nv_bfloat16*)d_in[3];
    const __nv_bfloat16* wv = (const __nv_bfloat16*)d_in[4];
    const __nv_bfloat16* wo = (const __nv_bfloat16*)d_in[5];
    const __nv_bfloat16* w1 = (const __nv_bfloat16*)d_in[8];
    const __nv_bfloat16* b1 = (const __nv_bfloat16*)d_in[9];
    const __nv_bfloat16* w2 = (const __nv_bfloat16*)d_in[10];
    const __nv_bfloat16* b2 = (const __nv_bfloat16*)d_in[11];
    const __nv_bfloat16* gw = (const __nv_bfloat16*)d_in[12];
    __nv_bfloat16* out = (__nv_bfloat16*)d_out;

    void* fn = nullptr;
    cudaDriverEntryPointQueryResult qr;
    cudaGetDriverEntryPoint("cuTensorMapEncodeTiled", &fn, cudaEnableDefault, &qr);
    EncodeFn enc = (EncodeFn)fn;
    void *ph = nullptr, *pox = nullptr;
    cudaGetSymbolAddress(&ph, g_h);
    cudaGetSymbolAddress(&pox, g_ox);

    CUtensorMap tm_x128, tm_w1, tm_h, tm_w2, tm_ox, tm_wo_b, tm_wq, tm_wk, tm_wv, tm_wo_a, tm_x32, tm_kv, tm_q;
    make_2d(enc, &tm_x128, x, S_, D_, 64, 128);
    make_2d(enc, &tm_w1, w1, D_, F_, 64, 64);
    make_2d(enc, &tm_h, ph, S_, F_, 64, 128);
    make_3d(enc, &tm_w2, w2, F_, D_, 64, 64, 2);
    make_2d(enc, &tm_ox, pox, S_, HD_, 64, 128);
    make_3d(enc, &tm_wo_b, wo, HD_, D_, 64, 64, 2);
    make_2d(enc, &tm_wq, wq, D_, HD_, 64, 256);
    make_2d(enc, &tm_wk, wk, D_, HD_, 64, 256);
    make_2d(enc, &tm_wv, wv, D_, HD_, 64, 256);
    make_2d(enc, &tm_wo_a, wo, HD_, D_, 64, 128);
    make_3d(enc, &tm_x32, x, S_, D_, 64, 32, 8);
    {
        void* pc = nullptr;
        cudaGetSymbolAddress(&pc, g_comm_raw);
        void* xp = (void*)((((uintptr_t)pc + 131071) & ~(uintptr_t)131071) + OFF_XP);
        cuuint64_t dims[3] = {256, 12, 256}; cuuint64_t str[2] = {1024, 12288};
        cuuint32_t box_kv[3] = {256, 8, 2}, box_q[3] = {256, 1, 2}, es[3] = {1, 1, 1};
        enc(&tm_kv, CU_TENSOR_MAP_DATA_TYPE_UINT32, 3, xp, dims, str, box_kv, es, CU_TENSOR_MAP_INTERLEAVE_NONE,
            CU_TENSOR_MAP_SWIZZLE_NONE, CU_TENSOR_MAP_L2_PROMOTION_NONE, CU_TENSOR_MAP_FLOAT_OOB_FILL_NONE);
        enc(&tm_q, CU_TENSOR_MAP_DATA_TYPE_UINT32, 3, xp, dims, str, box_q, es, CU_TENSOR_MAP_INTERLEAVE_NONE,
            CU_TENSOR_MAP_SWIZZLE_NONE, CU_TENSOR_MAP_L2_PROMOTION_NONE, CU_TENSOR_MAP_FLOAT_OOB_FILL_NONE);
    }

    cudaFuncSetAttribute(recur_kernel, cudaFuncAttributeMaxDynamicSharedMemorySize, R_SMEM);
    cudaFuncSetAttribute(dense_kernel, cudaFuncAttributeMaxDynamicSharedMemorySize, G_SMEM);

    cudaStream_t st = cudaStreamPerThread;
    recur_kernel<<<132, 256, R_SMEM, st>>>(tm_wq, tm_wk, tm_wv, tm_wo_a, tm_x32, tm_kv, tm_q, mem0, x, gw);
    cudaLaunchConfig_t cfg = {};
    cfg.gridDim = dim3(132); cfg.blockDim = dim3(384); cfg.dynamicSmemBytes = G_SMEM; cfg.stream = st;
    cudaLaunchAttribute at[1];
    at[0].id = cudaLaunchAttributeProgrammaticStreamSerialization; at[0].val.programmaticStreamSerializationAllowed = 1;
    cfg.attrs = at; cfg.numAttrs = PDL ? 1 : 0;
    cudaLaunchKernelEx(&cfg, dense_kernel, tm_x128, tm_w1, tm_h, tm_w2, tm_ox, tm_wo_b, b1, b2, out, (const unsigned char*)w1, (const unsigned char*)w2, (const unsigned char*)wo);
}
```
